```python
import torch

def _softmax(x, axis=-1):
    return torch.softmax(x, dim=axis)
def _gelu(x):
    return torch.nn.functional.gelu(x, approximate="tanh")
def _silu(x):
    return torch.nn.functional.silu(x)
def _sigmoid(x):
    return torch.sigmoid(x)
def _layernorm(x, axis=-1, eps=1e-5):
    m = x.mean(dim=axis, keepdim=True)
    v = x.var(dim=axis, keepdim=True, unbiased=False)
    return (x - m) / torch.sqrt(v + eps)
def _scatter_add(tgt, idx, src, axis=0):
    return tgt.clone().index_add_(axis, idx, src)
def _segment_sum(src, seg, n):
    out = torch.zeros((n,) + src.shape[1:], dtype=src.dtype)
    return out.index_add_(0, seg, src)
def _pad(x, pw):
    flat = tuple(v for pair in reversed(pw) for v in pair)
    return torch.nn.functional.pad(x, flat)

kernel_name = 'parallel_sum__ssm_conv_s4__glu_gated_bilinear__prompt'

def setup_inputs():

    _w = (lambda a: (lambda t: t.to(torch.bfloat16) if t.is_floating_point() else t)(torch.as_tensor(a)))
    def _A_setup():
        B, L, D, N = 1, 2048, 512, 128
        A_re = -(lambda _x: torch.exp(torch.as_tensor(_x)))((lambda *s: torch.randn(*s, dtype=torch.bfloat16) * 6.4)(D, N))
        A_im = torch.pi * (lambda *s: torch.randn(*s, dtype=torch.bfloat16) * 0.05)(D, N)
        B_re = (lambda *s: torch.randn(*s, dtype=torch.bfloat16) * 0.1)(D, N)
        B_im = (lambda *s: torch.randn(*s, dtype=torch.bfloat16) * 0.1)(D, N)
        C_re = (lambda *s: torch.randn(*s, dtype=torch.bfloat16) * 0.1)(D, N)
        C_im = (lambda *s: torch.randn(*s, dtype=torch.bfloat16) * 0.1)(D, N)
        log_dt = (lambda *s: torch.randn(*s, dtype=torch.bfloat16) * 0.05)(D) * 0.5 - 4.0
        Dskip = (lambda *s: torch.randn(*s, dtype=torch.bfloat16) * 0.05)(D)
        return {
            "u": _w((lambda *s: torch.randn(*s, dtype=torch.bfloat16) * 0.05)(B, L, D)),
            "A_re": _w(A_re),
            "A_im": _w(A_im),
            "B_re": _w(B_re),
            "B_im": _w(B_im),
            "C_re": _w(C_re),
            "C_im": _w(C_im),
            "log_dt": _w(log_dt),
            "Dskip": _w(Dskip),
        }
    _A_in = _A_setup()

    def _B_setup():
        B, S, D, F = 1, 2048, 512, 1376
        return {
            "x": _w((lambda *s: torch.randn(*s, dtype=torch.bfloat16) * 0.05)(B, S, D)),
            "w_gate": _w((lambda *s: torch.randn(*s, dtype=torch.bfloat16) * 0.4)(D, F) * (D ** -0.5)),
            "w_up": _w((lambda *s: torch.randn(*s, dtype=torch.bfloat16) * 0.4)(D, F) * (D ** -0.5)),
            "w_down": _w((lambda *s: torch.randn(*s, dtype=torch.bfloat16) * 0.4)(F, D) * (F ** -0.5)),
        }
    _B_in = _B_setup()

    return {
        "A_u": _A_in["u"],
        "A_A_re": _A_in["A_re"],
        "A_A_im": _A_in["A_im"],
        "A_B_re": _A_in["B_re"],
        "A_B_im": _A_in["B_im"],
        "A_C_re": _A_in["C_re"],
        "A_C_im": _A_in["C_im"],
        "A_log_dt": _A_in["log_dt"],
        "A_Dskip": _A_in["Dskip"],
        "B_x": _B_in["x"],
        "B_w_gate": _B_in["w_gate"],
        "B_w_up": _B_in["w_up"],
        "B_w_down": _B_in["w_down"],
    }

def reference(A_u, A_A_re, A_A_im, A_B_re, A_B_im, A_C_re, A_C_im, A_log_dt, A_Dskip, B_x, B_w_gate, B_w_up, B_w_down):
    def _A_ref(u, A_re, A_im, B_re, B_im, C_re, C_im, log_dt, Dskip):
        Bsz, L, D = u.shape
        dt = torch.exp(log_dt)[:, None]
        A = A_re + 1j * A_im
        Bc = B_re + 1j * B_im
        Cc = C_re + 1j * C_im
        logdA = dt * A
        dB = dt * Bc
        l = (lambda x, dt: x.to(dt))(torch.arange(L), A_re.dtype)
        P = torch.exp(logdA[:, :, None] * l[None, None, :])
        K = torch.einsum("dn,dnl,dn->dl", Cc, P, dB).real
        L2 = 2 * L
        Kp = _pad(K, ((0, 0), (0, L)))
        up = (lambda x, *d: x.permute(*d))(u, 0, 2, 1)
        up = _pad(up, ((0, 0), (0, 0), (0, L)))
        Kf = (lambda x, axes=(-2,-1): torch.fft.rfft2(x.float(), dim=axes))(Kp[:, None, :], axes=(-2, -1))
        Uf = (lambda x, axes=(-2,-1): torch.fft.rfft2(x.float(), dim=axes))(up[:, :, None, :], axes=(-2, -1))
        Yf = Uf * Kf[None, :, :, :]
        y = (lambda x, s, axes=(-2,-1): torch.fft.irfft2(x, s=s, dim=axes).to(torch.bfloat16))(Yf, (1, L2), axes=(-2, -1))[:, :, 0, :L]
        y = (lambda x, *d: x.permute(*d))(y, 0, 2, 1) + u * Dskip[None, None, :]
        return y

    def _B_ref(x, w_gate, w_up, w_down):
        g = torch.einsum("bsd,df->bsf", x, w_gate)
        u = torch.einsum("bsd,df->bsf", x, w_up)
        h = g * u
        return torch.einsum("bsf,fd->bsd", h, w_down)

    x = A_u
    xn = _layernorm(x, axis=-1)
    return x + _A_ref(xn, A_A_re, A_A_im, A_B_re, A_B_im, A_C_re, A_C_im, A_log_dt, A_Dskip) + _B_ref(xn, B_w_gate, B_w_up, B_w_down)
```

```cpp
#include <cuda_runtime.h>
#include <cuda_bf16.h>
#include <cuda.h>
#include <stdint.h>

namespace {

constexpr int T_ = 2048, D_ = 512, F_ = 1376;
constexpr int NTHREADS = 512;

constexpr uint32_t OFF_W = 0;
constexpr uint32_t OFF_X = 98304;
constexpr uint32_t OFF_S = 147456;
constexpr uint32_t SA_CH = 6400, S_5 = 0, S_3 = 3200, OFF_SB = OFF_S + 4 * SA_CH, SB_CH = 4096, S_9 = 0, S_7 = 2048;
constexpr uint32_t KG_DUMP = 2688;
constexpr uint32_t OFF_XT = 189440;
constexpr uint32_t OFF_TAP = 206848;
constexpr uint32_t TAP_CH = 3584, TAP_5 = 2176, TAP_3 = 2528, TAP_9 = 2880, TAP_7 = 3232;
constexpr uint32_t OFF_FIX = 229376;
constexpr uint32_t OFF_AUX = 221184;
constexpr uint32_t OFF_YS = 180224, YS_STEP = OFF_AUX - OFF_YS;
constexpr uint32_t OFF_MID = OFF_S;
__host__ __device__ constexpr uint32_t hslot(int i) { return i < 2 ? i * 16384 : i == 2 ? 65536 : i == 3 ? 32768 : i == 4 ? 90112 : i == 5 ? 49152 : 106496; }
constexpr uint32_t HSEQ = 0x20d6b482;
constexpr uint32_t OFF_STAT = 230144;
constexpr uint32_t OFF_MISC = 230656;
constexpr uint32_t OFF_BAR = 230976;
constexpr uint32_t SMEM_BYTES = OFF_BAR + 896 + 512;
constexpr int B_KG = 17, B_F1 = 0,
              B_C1 = 18, B_CS = 35;
constexpr int B_XT = 36, B_Y = 37, B_XR = 38, B_LN = 39, B_PART = 40, B_HT = 41, B_H01 = 42,
              B_F2 = 45, B_C2 = 61, B_STG = 70, B_PF = 71,
              B_BOX = 72, B_ST = 73, B_XRD = 79, B_LNST = 82, B_STG2 = 83, B_CONV = 84,
              B_YST = 85,
              B_HM = 99, B_YP = 100;

constexpr size_t G_XT = 0;
constexpr size_t G_YT = G_XT + 2 * D_ * T_;
constexpr size_t G_H = G_YT + 2 * D_ * T_;
constexpr size_t G_WEXT = G_H + 16 * 24 * 16384;
constexpr size_t G_NEGM = G_WEXT + 32 * 1536 * 2;
constexpr size_t G_R2 = G_NEGM + T_ * 16;
constexpr size_t G_CNT = G_R2 + T_ * 4;
constexpr int C_LN = 0, C_H = 32, C_Y = 128, C_EP = 136;
__device__ __align__(1024) uint8_t g_scr[G_CNT + 137 * 256];
constexpr bool TRACE_ALL = false;
#define TR(i) do {} while (0)
#define TR2(i) do {} while (0)
#define TRC(c, i) do {} while (0)
#define TREND() do {} while (0)

struct Params {
  const __nv_bfloat16 *ssm[7], *dskip, *xp;
  uint8_t* scr;
  CUtensorMap x, wg, wu, wext, w2, w2s, xt, yt, out;
};

constexpr int SPIN_LIMIT = 1 << 13;
#define RING_NS 150
#define WGSWAP 0
#define HORD 1
#define PASSJ 8
#define DEFP 0
#define OP 2
#define CSMODE 1
#define WPF 0
#define XPF 1
constexpr int CSS = CSMODE ? 0 : 2;
#define XMID 0
#define W2PF 2
#define GFENCE 1
#define XPOS 1
#define P2LATE 0
#define OUTPF 1
#define GPOS 0
#define FCMAP 1
#define YU 11
#define XT_NS 30
#define POLL_NS 20

__device__ __forceinline__ void mbar_init(uint32_t b, int c) { asm volatile("mbarrier.init.shared::cta.b64 [%0], %1;" ::"r"(b), "r"(c) : "memory"); }
__device__ __forceinline__ void mbar_expect(uint32_t b, int bytes) { asm volatile("mbarrier.arrive.expect_tx.shared::cta.b64 _, [%0], %1;" ::"r"(b), "r"(bytes) : "memory"); }
__device__ __forceinline__ void mbar_arrive(uint32_t b) { asm volatile("mbarrier.arrive.shared::cta.b64 _, [%0];" ::"r"(b) : "memory"); }
__device__ __forceinline__ void mbar_arrive_cl(uint32_t b, uint32_t cta) {
  asm volatile("{.reg .b32 r; mapa.shared::cluster.u32 r, %0, %1; mbarrier.arrive.shared::cluster.b64 _, [r];}" ::"r"(b), "r"(cta) : "memory");
}
__device__ __forceinline__ void mbar_wait(uint32_t b) {
  asm volatile(
      "{.reg .pred p, q; .reg .u32 n; mov.u32 n, 0;\n"
      "W: mbarrier.try_wait.parity.shared::cta.b64 p, [%0], 0;\n"
      "@p bra D;\n"
      "add.u32 n, n, 1; setp.lt.u32 q, n, %1;\n"
      "@q bra W;\n"
      "D:}" ::"r"(b), "n"(SPIN_LIMIT) : "memory");
}
__device__ __forceinline__ bool elect() {
  uint32_t e;
  asm volatile("{.reg .pred p; elect.sync _|p, 0xffffffff; selp.u32 %0, 1, 0, p;}" : "=r"(e));
  return e;
}
__device__ __forceinline__ void tma2d(uint32_t dst, const CUtensorMap* tm, uint32_t bar, int c0, int c1) {
  asm volatile("cp.async.bulk.tensor.2d.shared::cluster.global.mbarrier::complete_tx::bytes [%0], [%1, {%3,%4}], [%2];"
               ::"r"(dst), "l"(tm), "r"(bar), "r"(c0), "r"(c1) : "memory");
}
__device__ __forceinline__ void tma2d_mc(uint32_t dst, const CUtensorMap* tm, uint32_t bar, int c0, int c1) {
  asm volatile("cp.async.bulk.tensor.2d.shared::cluster.global.mbarrier::complete_tx::bytes.multicast::cluster [%0], [%1, {%3,%4}], [%2], %5;"
               ::"r"(dst), "l"(tm), "r"(bar), "r"(c0), "r"(c1), "h"((uint16_t)3) : "memory");
}
__device__ __forceinline__ void tma2d_st(const CUtensorMap* tm, uint32_t src, int c0, int c1) {
  asm volatile("cp.async.bulk.tensor.2d.global.shared::cta.bulk_group [%0, {%2,%3}], [%1];" ::"l"(tm), "r"(src), "r"(c0), "r"(c1) : "memory");
}
__device__ __forceinline__ void tma2d_pf(const CUtensorMap* tm, int c0, int c1) {
  asm volatile("cp.async.bulk.prefetch.tensor.2d.L2.global [%0, {%1,%2}];" ::"l"(tm), "r"(c0), "r"(c1) : "memory");
}
__device__ __forceinline__ void bulk_ld(uint32_t dst, const void* src, int bytes, uint32_t bar) {
  asm volatile("cp.async.bulk.shared::cluster.global.mbarrier::complete_tx::bytes [%0], [%1], %2, [%3];" ::"r"(dst), "l"(src), "r"(bytes), "r"(bar) : "memory");
}
__device__ __forceinline__ void bulk_st(void* dst, uint32_t src, int bytes) {
  asm volatile("cp.async.bulk.global.shared::cta.bulk_group [%0], [%1], %2;" ::"l"(dst), "r"(src), "r"(bytes) : "memory");
}
__device__ __forceinline__ void bulk_commit() { asm volatile("cp.async.bulk.commit_group;" ::: "memory"); }
__device__ __forceinline__ void bulk_wait_read() { asm volatile("cp.async.bulk.wait_group.read 0;" ::: "memory"); }
template <int N> __device__ __forceinline__ void bulk_wait() { asm volatile("cp.async.bulk.wait_group %0;" ::"n"(N) : "memory"); }
__device__ __forceinline__ void fence_async_smem() { asm volatile("fence.proxy.async.shared::cta;" ::: "memory"); }
__device__ __forceinline__ void fence_async_gmem() { if (GFENCE) asm volatile("fence.proxy.async.global;" ::: "memory"); }
template <int ID, int N = 128> __device__ __forceinline__ void bar_sync() { asm volatile("bar.sync %0, %1;" ::"n"(ID), "n"(N) : "memory"); }
__device__ __forceinline__ void signal(uint8_t* scr, int cnt) {
  asm volatile("red.relaxed.gpu.global.add.u32 [%0], 1;" ::"l"(scr + G_CNT + cnt * 256) : "memory");
}
__device__ __forceinline__ uint32_t ld_relaxed(const void* p) {
  uint32_t v;
  asm volatile("ld.relaxed.gpu.global.u32 %0, [%1];" : "=r"(v) : "l"(p) : "memory");
  return v;
}
__device__ __forceinline__ void poll(const uint8_t* scr, int cnt, uint32_t target) {
#pragma unroll 1
  for (int it = 0; it < SPIN_LIMIT * 4; it++) {
    if (__all_sync(0xffffffffu, (int)(ld_relaxed(scr + G_CNT + cnt * 256) - target) >= 0)) break;
    __nanosleep(POLL_NS);
  }
  asm volatile("fence.acquire.gpu;" ::: "memory");
  fence_async_gmem();
}
__device__ __forceinline__ void wg_fence() { asm volatile("wgmma.fence.sync.aligned;" ::: "memory"); }
__device__ __forceinline__ void wg_commit() { asm volatile("wgmma.commit_group.sync.aligned;" ::: "memory"); }
template <int N> __device__ __forceinline__ void wg_wait() { asm volatile("wgmma.wait_group.sync.aligned %0;" ::"n"(N) : "memory"); }
constexpr uint32_t SB0 = 1024;
__device__ __forceinline__ constexpr uint32_t mkdesc(uint32_t off, uint32_t lbo) { return ((SB0 + off) >> 4) | ((lbo >> 4) << 16); }
__device__ __forceinline__ void wgmma176_ss(float (&d)[88], uint32_t da, uint32_t db, int acc) {
  asm volatile("{.reg .pred p; .reg .b64 a, b; setp.ne.b32 p, %90, 0; mov.b64 a, {%88, 0x40000040}; mov.b64 b, {%89, 0x40000040};\n"
    "wgmma.mma_async.sync.aligned.m64n176k16.f32.bf16.bf16 {%0,%1,%2,%3,%4,%5,%6,%7,%8,%9,%10,%11,%12,%13,%14,%15,%16,%17,%18,%19,%20,%21,%22,%23,%24,%25,%26,%27,%28,%29,%30,%31,%32,%33,%34,%35,%36,%37,%38,%39,%40,%41,%42,%43,%44,%45,%46,%47,%48,%49,%50,%51,%52,%53,%54,%55,%56,%57,%58,%59,%60,%61,%62,%63,%64,%65,%66,%67,%68,%69,%70,%71,%72,%73,%74,%75,%76,%77,%78,%79,%80,%81,%82,%83,%84,%85,%86,%87}, a, b, p, 1, 1, 0, 1;}\n"
    : "+f"(d[0]),"+f"(d[1]),"+f"(d[2]),"+f"(d[3]),"+f"(d[4]),"+f"(d[5]),"+f"(d[6]),"+f"(d[7]),"+f"(d[8]),"+f"(d[9]),"+f"(d[10]),"+f"(d[11]),"+f"(d[12]),"+f"(d[13]),"+f"(d[14]),"+f"(d[15]),"+f"(d[16]),"+f"(d[17]),"+f"(d[18]),"+f"(d[19]),"+f"(d[20]),"+f"(d[21]),"+f"(d[22]),"+f"(d[23]),"+f"(d[24]),"+f"(d[25]),"+f"(d[26]),"+f"(d[27]),"+f"(d[28]),"+f"(d[29]),"+f"(d[30]),"+f"(d[31]),"+f"(d[32]),"+f"(d[33]),"+f"(d[34]),"+f"(d[35]),"+f"(d[36]),"+f"(d[37]),"+f"(d[38]),"+f"(d[39]),"+f"(d[40]),"+f"(d[41]),"+f"(d[42]),"+f"(d[43]),"+f"(d[44]),"+f"(d[45]),"+f"(d[46]),"+f"(d[47]),"+f"(d[48]),"+f"(d[49]),"+f"(d[50]),"+f"(d[51]),"+f"(d[52]),"+f"(d[53]),"+f"(d[54]),"+f"(d[55]),"+f"(d[56]),"+f"(d[57]),"+f"(d[58]),"+f"(d[59]),"+f"(d[60]),"+f"(d[61]),"+f"(d[62]),"+f"(d[63]),"+f"(d[64]),"+f"(d[65]),"+f"(d[66]),"+f"(d[67]),"+f"(d[68]),"+f"(d[69]),"+f"(d[70]),"+f"(d[71]),"+f"(d[72]),"+f"(d[73]),"+f"(d[74]),"+f"(d[75]),"+f"(d[76]),"+f"(d[77]),"+f"(d[78]),"+f"(d[79]),"+f"(d[80]),"+f"(d[81]),"+f"(d[82]),"+f"(d[83]),"+f"(d[84]),"+f"(d[85]),"+f"(d[86]),"+f"(d[87])
    : "r"(da), "r"(db), "r"(acc));
}
__device__ __forceinline__ void wgmma176_ns(float (&d)[88], uint32_t da, uint32_t db, int acc) {
  asm volatile("{.reg .pred p; .reg .b64 a, b; setp.ne.b32 p, %90, 0; mov.b64 a, {%88, 0x00000008}; mov.b64 b, {%89, 0x40000040};\n"
    "wgmma.mma_async.sync.aligned.m64n176k16.f32.bf16.bf16 {%0,%1,%2,%3,%4,%5,%6,%7,%8,%9,%10,%11,%12,%13,%14,%15,%16,%17,%18,%19,%20,%21,%22,%23,%24,%25,%26,%27,%28,%29,%30,%31,%32,%33,%34,%35,%36,%37,%38,%39,%40,%41,%42,%43,%44,%45,%46,%47,%48,%49,%50,%51,%52,%53,%54,%55,%56,%57,%58,%59,%60,%61,%62,%63,%64,%65,%66,%67,%68,%69,%70,%71,%72,%73,%74,%75,%76,%77,%78,%79,%80,%81,%82,%83,%84,%85,%86,%87}, a, b, p, 1, 1, 0, 1;}\n"
    : "+f"(d[0]),"+f"(d[1]),"+f"(d[2]),"+f"(d[3]),"+f"(d[4]),"+f"(d[5]),"+f"(d[6]),"+f"(d[7]),"+f"(d[8]),"+f"(d[9]),"+f"(d[10]),"+f"(d[11]),"+f"(d[12]),"+f"(d[13]),"+f"(d[14]),"+f"(d[15]),"+f"(d[16]),"+f"(d[17]),"+f"(d[18]),"+f"(d[19]),"+f"(d[20]),"+f"(d[21]),"+f"(d[22]),"+f"(d[23]),"+f"(d[24]),"+f"(d[25]),"+f"(d[26]),"+f"(d[27]),"+f"(d[28]),"+f"(d[29]),"+f"(d[30]),"+f"(d[31]),"+f"(d[32]),"+f"(d[33]),"+f"(d[34]),"+f"(d[35]),"+f"(d[36]),"+f"(d[37]),"+f"(d[38]),"+f"(d[39]),"+f"(d[40]),"+f"(d[41]),"+f"(d[42]),"+f"(d[43]),"+f"(d[44]),"+f"(d[45]),"+f"(d[46]),"+f"(d[47]),"+f"(d[48]),"+f"(d[49]),"+f"(d[50]),"+f"(d[51]),"+f"(d[52]),"+f"(d[53]),"+f"(d[54]),"+f"(d[55]),"+f"(d[56]),"+f"(d[57]),"+f"(d[58]),"+f"(d[59]),"+f"(d[60]),"+f"(d[61]),"+f"(d[62]),"+f"(d[63]),"+f"(d[64]),"+f"(d[65]),"+f"(d[66]),"+f"(d[67]),"+f"(d[68]),"+f"(d[69]),"+f"(d[70]),"+f"(d[71]),"+f"(d[72]),"+f"(d[73]),"+f"(d[74]),"+f"(d[75]),"+f"(d[76]),"+f"(d[77]),"+f"(d[78]),"+f"(d[79]),"+f"(d[80]),"+f"(d[81]),"+f"(d[82]),"+f"(d[83]),"+f"(d[84]),"+f"(d[85]),"+f"(d[86]),"+f"(d[87])
    : "r"(da), "r"(db), "r"(acc));
}
template <int SBO> __device__ __forceinline__ void wgmma128_t(float (&d)[64], uint32_t da, uint32_t db, int acc) {
  asm volatile("{.reg .pred p; .reg .b64 a, b; setp.ne.b32 p, %66, 0; mov.b64 a, {%64, 0x40000040}; mov.b64 b, {%65, %67};\n"
    "wgmma.mma_async.sync.aligned.m64n128k16.f32.bf16.bf16 {%0,%1,%2,%3,%4,%5,%6,%7,%8,%9,%10,%11,%12,%13,%14,%15,%16,%17,%18,%19,%20,%21,%22,%23,%24,%25,%26,%27,%28,%29,%30,%31,%32,%33,%34,%35,%36,%37,%38,%39,%40,%41,%42,%43,%44,%45,%46,%47,%48,%49,%50,%51,%52,%53,%54,%55,%56,%57,%58,%59,%60,%61,%62,%63}, a, b, p, 1, 1, 1, 0;}\n"
    : "+f"(d[0]),"+f"(d[1]),"+f"(d[2]),"+f"(d[3]),"+f"(d[4]),"+f"(d[5]),"+f"(d[6]),"+f"(d[7]),"+f"(d[8]),"+f"(d[9]),"+f"(d[10]),"+f"(d[11]),"+f"(d[12]),"+f"(d[13]),"+f"(d[14]),"+f"(d[15]),"+f"(d[16]),"+f"(d[17]),"+f"(d[18]),"+f"(d[19]),"+f"(d[20]),"+f"(d[21]),"+f"(d[22]),"+f"(d[23]),"+f"(d[24]),"+f"(d[25]),"+f"(d[26]),"+f"(d[27]),"+f"(d[28]),"+f"(d[29]),"+f"(d[30]),"+f"(d[31]),"+f"(d[32]),"+f"(d[33]),"+f"(d[34]),"+f"(d[35]),"+f"(d[36]),"+f"(d[37]),"+f"(d[38]),"+f"(d[39]),"+f"(d[40]),"+f"(d[41]),"+f"(d[42]),"+f"(d[43]),"+f"(d[44]),"+f"(d[45]),"+f"(d[46]),"+f"(d[47]),"+f"(d[48]),"+f"(d[49]),"+f"(d[50]),"+f"(d[51]),"+f"(d[52]),"+f"(d[53]),"+f"(d[54]),"+f"(d[55]),"+f"(d[56]),"+f"(d[57]),"+f"(d[58]),"+f"(d[59]),"+f"(d[60]),"+f"(d[61]),"+f"(d[62]),"+f"(d[63])
    : "r"(da), "r"(db), "r"(acc), "n"(SBO >> 4));
}
__device__ __forceinline__ void wgmma8_t(float (&d)[4], uint32_t da, uint32_t db, int acc) {
  asm volatile("{.reg .pred p; .reg .b64 a, b; setp.ne.b32 p, %6, 0; mov.b64 a, {%4, 0x40000040}; mov.b64 b, {%5, 0x00000008};\n"
    "wgmma.mma_async.sync.aligned.m64n8k16.f32.bf16.bf16 {%0,%1,%2,%3}, a, b, p, 1, 1, 1, 0;}\n"
    : "+f"(d[0]),"+f"(d[1]),"+f"(d[2]),"+f"(d[3])
    : "r"(da), "r"(db), "r"(acc));
}
template <int ACC> __device__ __forceinline__ void wgmma128_rs(float (&d)[64], const uint32_t (&a)[4], uint32_t db) {
  asm volatile("{.reg .b64 b; mov.b64 b, {%68, 0x40000040};\n"
    "wgmma.mma_async.sync.aligned.m64n128k16.f32.bf16.bf16 {%0,%1,%2,%3,%4,%5,%6,%7,%8,%9,%10,%11,%12,%13,%14,%15,%16,%17,%18,%19,%20,%21,%22,%23,%24,%25,%26,%27,%28,%29,%30,%31,%32,%33,%34,%35,%36,%37,%38,%39,%40,%41,%42,%43,%44,%45,%46,%47,%48,%49,%50,%51,%52,%53,%54,%55,%56,%57,%58,%59,%60,%61,%62,%63}, {%64,%65,%66,%67}, b, %69, 1, 1, 0;}\n"
    : "+f"(d[0]),"+f"(d[1]),"+f"(d[2]),"+f"(d[3]),"+f"(d[4]),"+f"(d[5]),"+f"(d[6]),"+f"(d[7]),"+f"(d[8]),"+f"(d[9]),"+f"(d[10]),"+f"(d[11]),"+f"(d[12]),"+f"(d[13]),"+f"(d[14]),"+f"(d[15]),"+f"(d[16]),"+f"(d[17]),"+f"(d[18]),"+f"(d[19]),"+f"(d[20]),"+f"(d[21]),"+f"(d[22]),"+f"(d[23]),"+f"(d[24]),"+f"(d[25]),"+f"(d[26]),"+f"(d[27]),"+f"(d[28]),"+f"(d[29]),"+f"(d[30]),"+f"(d[31]),"+f"(d[32]),"+f"(d[33]),"+f"(d[34]),"+f"(d[35]),"+f"(d[36]),"+f"(d[37]),"+f"(d[38]),"+f"(d[39]),"+f"(d[40]),"+f"(d[41]),"+f"(d[42]),"+f"(d[43]),"+f"(d[44]),"+f"(d[45]),"+f"(d[46]),"+f"(d[47]),"+f"(d[48]),"+f"(d[49]),"+f"(d[50]),"+f"(d[51]),"+f"(d[52]),"+f"(d[53]),"+f"(d[54]),"+f"(d[55]),"+f"(d[56]),"+f"(d[57]),"+f"(d[58]),"+f"(d[59]),"+f"(d[60]),"+f"(d[61]),"+f"(d[62]),"+f"(d[63])
    : "r"(a[0]), "r"(a[1]), "r"(a[2]), "r"(a[3]), "r"(db), "n"(ACC));
}

__device__ __forceinline__ void mma16816(float (&d)[4], uint32_t a0, uint32_t a1, uint32_t a2, uint32_t a3, uint32_t b0, uint32_t b1) {
  asm volatile("mma.sync.aligned.m16n8k16.row.col.f32.bf16.bf16.f32 {%0,%1,%2,%3}, {%4,%5,%6,%7}, {%8,%9}, {%0,%1,%2,%3};"
               : "+f"(d[0]), "+f"(d[1]), "+f"(d[2]), "+f"(d[3]) : "r"(a0), "r"(a1), "r"(a2), "r"(a3), "r"(b0), "r"(b1));
}
__device__ __forceinline__ void ldsm4(uint32_t& r0, uint32_t& r1, uint32_t& r2, uint32_t& r3, uint32_t a) {
  asm volatile("ldmatrix.sync.aligned.m8n8.x4.shared.b16 {%0,%1,%2,%3}, [%4];" : "=r"(r0), "=r"(r1), "=r"(r2), "=r"(r3) : "r"(a) : "memory");
}
__device__ __forceinline__ void ldsm4t(uint32_t& r0, uint32_t& r1, uint32_t& r2, uint32_t& r3, uint32_t a) {
  asm volatile("ldmatrix.sync.aligned.m8n8.x4.trans.shared.b16 {%0,%1,%2,%3}, [%4];" : "=r"(r0), "=r"(r1), "=r"(r2), "=r"(r3) : "r"(a) : "memory");
}
__device__ __forceinline__ void ldsm2t(uint32_t& r0, uint32_t& r1, uint32_t a) {
  asm volatile("ldmatrix.sync.aligned.m8n8.x2.trans.shared.b16 {%0,%1}, [%2];" : "=r"(r0), "=r"(r1) : "r"(a) : "memory");
}
__device__ __forceinline__ void stsm2(uint32_t a, uint32_t r0, uint32_t r1) {
  asm volatile("stmatrix.sync.aligned.m8n8.x2.shared.b16 [%0], {%1,%2};" ::"r"(a), "r"(r0), "r"(r1) : "memory");
}
__device__ __forceinline__ void stsm4(uint32_t a, uint32_t r0, uint32_t r1, uint32_t r2, uint32_t r3) {
  asm volatile("stmatrix.sync.aligned.m8n8.x4.shared.b16 [%0], {%1,%2,%3,%4};" ::"r"(a), "r"(r0), "r"(r1), "r"(r2), "r"(r3) : "memory");
}
__device__ __forceinline__ void stsm4t(uint32_t a, uint32_t r0, uint32_t r1, uint32_t r2, uint32_t r3) {
  asm volatile("stmatrix.sync.aligned.m8n8.x4.trans.shared.b16 [%0], {%1,%2,%3,%4};" ::"r"(a), "r"(r0), "r"(r1), "r"(r2), "r"(r3) : "memory");
}
__device__ __forceinline__ uint32_t lds32(uint32_t a) { uint32_t v; asm volatile("ld.shared.u32 %0, [%1];" : "=r"(v) : "r"(a) : "memory"); return v; }
__device__ __forceinline__ uint32_t lds16(uint32_t a) { uint16_t v; asm volatile("ld.shared.u16 %0, [%1];" : "=h"(v) : "r"(a) : "memory"); return v; }
__device__ __forceinline__ uint2 lds64(uint32_t a) { uint2 v; asm volatile("ld.shared.v2.u32 {%0,%1}, [%2];" : "=r"(v.x), "=r"(v.y) : "r"(a) : "memory"); return v; }
__device__ __forceinline__ uint4 lds128(uint32_t a) { uint4 v; asm volatile("ld.shared.v4.u32 {%0,%1,%2,%3}, [%4];" : "=r"(v.x), "=r"(v.y), "=r"(v.z), "=r"(v.w) : "r"(a) : "memory"); return v; }
__device__ __forceinline__ void sts16(uint32_t a, uint32_t v) { asm volatile("st.shared.u16 [%0], %1;" ::"r"(a), "h"((uint16_t)v) : "memory"); }
__device__ __forceinline__ void sts32(uint32_t a, uint32_t v) { asm volatile("st.shared.u32 [%0], %1;" ::"r"(a), "r"(v) : "memory"); }
__device__ __forceinline__ void sts64(uint32_t a, uint32_t x, uint32_t y) { asm volatile("st.shared.v2.u32 [%0], {%1,%2};" ::"r"(a), "r"(x), "r"(y) : "memory"); }
__device__ __forceinline__ void sts128(uint32_t a, uint32_t x, uint32_t y, uint32_t z, uint32_t w) {
  asm volatile("st.shared.v4.u32 [%0], {%1,%2,%3,%4};" ::"r"(a), "r"(x), "r"(y), "r"(z), "r"(w) : "memory");
}
__device__ __forceinline__ uint32_t pack2(float lo, float hi) { uint32_t r; asm("cvt.rn.bf16x2.f32 %0, %1, %2;" : "=r"(r) : "f"(hi), "f"(lo)); return r; }
__device__ __forceinline__ uint32_t hadd2(uint32_t a, uint32_t b) { uint32_t r; asm("add.rn.bf16x2 %0, %1, %2;" : "=r"(r) : "r"(a), "r"(b)); return r; }
__device__ __forceinline__ float bf_lo(uint32_t v) { return __uint_as_float(v << 16); }
__device__ __forceinline__ float bf_hi(uint32_t v) { return __uint_as_float(v & 0xffff0000u); }
__device__ __forceinline__ float bf_round(float v) { return bf_lo(pack2(v, 0.f)); }
__device__ __forceinline__ uint32_t swz(uint32_t a) { return a ^ ((a >> 3) & 0x70); }
__device__ __forceinline__ int cpos(int ch, int half) { return 2 * ch + half; }

struct cf { float r, i; };
__device__ __forceinline__ cf cmul(cf a, cf b) { return cf{fmaf(-a.i, b.i, a.r * b.r), fmaf(a.i, b.r, a.r * b.i)}; }
__device__ __forceinline__ cf csq(cf a) { return cf{fmaf(a.r, a.r, -a.i * a.i), (a.r + a.r) * a.i}; }
__device__ __forceinline__ cf cexp_pow2(float zl, float hi, float lo, float e) {
  float h = hi * e;
  float f = fmaf(lo, e, h - rintf(h)) * 6.283185307179586f;
  float m;
  asm("ex2.approx.ftz.f32 %0, %1;" : "=f"(m) : "f"(zl * e));
  return cf{m * __cosf(f), m * __sinf(f)};
}

template <class F> __device__ __forceinline__ void conv_mid(uint32_t sb, int ch, int lane, float (&r)[13][4], F side) {
  const int g = lane >> 2, c = lane & 3;
  const uint32_t S = sb + OFF_S + ch * SA_CH, TAP = sb + OFF_TAP + ch * TAP_CH, tp = TAP + (g - 2 * c) * 4;
  const uint32_t z0 = lds32(TAP);
#pragma unroll
  for (int p = 0; p < 13; p++) r[p][0] = r[p][1] = r[p][2] = r[p][3] = 0.f;
#pragma unroll
  for (int cls = 0; cls < 2; cls++) {
    uint32_t x[13][2];
#pragma unroll
    for (int p = 0; p < 12; p += 2) ldsm4t(x[p + 1][0], x[p + 1][1], x[p + 2][0], x[p + 2][1], S + (cls ? S_3 : S_5) + 128 + p * 256 + lane * 16);
    if (cls == 0) ldsm2t(x[0][0], x[0][1], S + ((lane & 8) ? S_5 : S_3) + (lane & 7) * 16);
    uint32_t a1 = z0;
#pragma unroll
    for (int m = 4; m <= 8; m++) {
      const uint32_t a2 = a1 + z0, a0 = lds32(tp + (cls ? TAP_3 : TAP_5) + (2 * m - 7) * 32), a3 = a0 + z0;
      a1 = lds32(tp + (cls ? TAP_3 : TAP_5) + (2 * m - 6) * 32);
      if (m < 8) { side(cls * 8 + 2 * (m - 4)); side(cls * 8 + 2 * (m - 4) + 1); }
#pragma unroll
      for (int pm = cls - 1; pm + m < 16; pm++) mma16816(r[m + pm - 3], a0, a1, a2, a3, x[pm + 1][0], x[pm + 1][1]);
    }
  }
}
template <class F> __device__ __forceinline__ void conv_far(uint32_t sb, int ch, int lane, float (&acc)[12][4], F side) {
  const int g = lane >> 2, c = lane & 3, mi = lane >> 3, n = lane & 7;
  const uint32_t S = sb + OFF_SB + ch * SB_CH, TAP = sb + OFF_TAP + ch * TAP_CH;
  const uint32_t z0 = lds32(TAP);
#pragma unroll
  for (int p = 0; p < 12; p++) acc[p][0] = acc[p][1] = acc[p][2] = acc[p][3] = 0.f;
#pragma unroll
  for (int cls = 0; cls < 2; cls++) {
    const uint32_t tp = TAP + TAP_9 + 4 + cls * (TAP_7 - TAP_9 - 4) + (g - 2 * c + 8) * 4;
    uint32_t u[8][2];
    u[0][1] = lds32(tp);
#pragma unroll
    for (int i = 0; i < 8; i++) { u[i][0] = lds32(tp + i * 32 + 32); if (i < 7) u[i + 1][1] = u[i][0] + z0; }
    const uint32_t sp = S + S_9 + cls * (S_7 - S_9) + (mi & 1) * 1024 + (mi >> 1) * 128 + n * 16;
#pragma unroll
    for (int s = 0; s < 4; s++) {
      uint32_t a0, a1, a2, a3;
      ldsm4t(a0, a1, a2, a3, sp + s * 256);
      side(cls * 4 + s);
#pragma unroll
      for (int p = 2 * s; p < 8; p++) mma16816(acc[4 + p], a0, a1, a2, a3, u[p - 2 * s][0], u[p - 2 * s][1]);
    }
  }
  const uint32_t pp = TAP + (16 + 512 + g - 2 * c) * 4, fp = sb + OFF_FIX + ch * 192 + (g - 2 * c + 16) * 4;
  const uint32_t xl = sb + OFF_XT + 1024 + (8 * (mi >> 1) + n) * 128 + cpos(ch, mi & 1) * 16, xa = swz(xl), xb = swz(xl - 128);
  const uint32_t a0 = lds32(pp), a1 = lds32(pp + 32), a2 = lds32(pp - 32), a3 = a0 + z0;
  const uint32_t f0 = lds32(fp), f1 = lds32(fp + 32), f2 = lds32(fp - 32), f3 = f0 + z0;
  const uint32_t e0 = lds32(fp + 64), e1 = lds32(fp + 96), e2 = f1 + z0, e3 = e0 + z0;
#pragma unroll
  for (int p = 0; p < 12; p += 2) {
    uint32_t b0, b1, b2, b3;
    ldsm4(b0, b1, b2, b3, xa + p * 1024);
    side(8 + p / 2);
    mma16816(acc[p], a0, a1, a2, a3, b0, b1);
    mma16816(acc[p + 1], a0, a1, a2, a3, b2, b3);
    if (p < 8) {
      mma16816(acc[4 + p], f0, f1, f2, f3, b0, b1);
      mma16816(acc[5 + p], f0, f1, f2, f3, b2, b3);
    }
  }
#pragma unroll
  for (int p = 0; p < 8; p += 2) {
    uint32_t b0, b1, b2, b3;
    ldsm4(b0, b1, b2, b3, xb + p * 1024);
    if (p < 4) side(14 + p / 2);
    mma16816(acc[4 + p], e0, e1, e2, e3, b0, b1);
    mma16816(acc[5 + p], e0, e1, e2, e3, b2, b3);
  }
}

template <class F> __device__ __forceinline__ void kgen(uint32_t sb, int warp, int lane, const uint32_t (&pa)[7], F midway) {
  const int mi = lane >> 3, n = lane & 7;
  const float dt = bf_round(expf(bf_lo(pa[6])));
  const uint32_t sa = sb + OFF_S + warp * KG_DUMP, sq = sb + (warp < 8 ? OFF_X + 32768 : OFF_XT + 1024 - 16384) + warp * 2048;
  TRC(dt != 123.f, 50);
  const float zl = (dt * bf_lo(pa[0])) * 1.4426950408889634f, zi = dt * bf_lo(pa[1]);
  const float hi = zi * 0.15915494f;
  const float lo = fmaf(zi, 6.4206382e-9f, fmaf(zi, 0.15915494f, -hi));
  const cf w1 = cexp_pow2(zl, hi, lo, 1.f), w128 = cexp_pow2(zl, hi, lo, 128.f);
  const cf w2 = csq(w1), w4 = csq(w2), w8 = csq(w4);
  cf q = cmul(cf{bf_lo(pa[4]), bf_lo(pa[5])}, cf{dt * bf_lo(pa[2]), dt * bf_lo(pa[3])});
  TRC(w1.r + q.r != 123.f, 48);
  const cf w8c{w8.r, -w8.i};
  cf u{1.f, 0.f};
  float kk[5][4];
  auto gen = [&](int set) {
    cf v[8];
    if (set < 2) {
#pragma unroll
      for (int i = 0; i < 8; i++) {
        if (set == 0 && i == 1) u = w8c;
        else if (set + i > 0) u = cmul(u, w8c);
        v[i] = u;
      }
    } else {
      const int step = set < 4 ? 8 : set == 4 ? 4 : set == 5 ? 2 : 1;
      const cf ws = set < 4 ? w1 : set == 4 ? w2 : w4;
#pragma unroll
      for (int i = 0; i < 8; i++) {
        if (i % step == 0) { if (set + i > 2) q = cmul(q, w128); v[i] = q; }
        else v[i] = cmul(v[i - 1], ws);
      }
    }
    const uint32_t sp = (set < 2 ? sa : sq) + lane * 16 + (set & 1) * 1024;
    sts128(sp, pack2(v[0].r, v[1].r), pack2(v[2].r, v[3].r), pack2(v[4].r, v[5].r), pack2(v[6].r, v[7].r));
    sts128(sp + 512, pack2(v[0].i, v[1].i), pack2(v[2].i, v[3].i), pack2(v[4].i, v[5].i), pack2(v[6].i, v[7].i));
    __syncwarp();
  };
  uint32_t a[4][4];
  auto use = [&](int t) {
    uint32_t b[8];
    const uint32_t sp = sq + (t & 1) * 1024 + (mi & 1) * 512 + (mi >> 1) * 128 + n * 16;
    ldsm4t(b[0], b[1], b[2], b[3], sp);
    ldsm4t(b[4], b[5], b[6], b[7], sp + 256);
    __syncwarp();
    kk[t][0] = kk[t][1] = kk[t][2] = kk[t][3] = 0.f;
#pragma unroll
    for (int s = 0; s < 4; s++) mma16816(kk[t], a[s][0], a[s][1], a[s][2], a[s][3], b[2 * s], b[2 * s + 1]);
  };
#define SPLIT(i) if (warp == 16 + (i)) asm volatile("trap;")
  gen(0); SPLIT(0); gen(1); SPLIT(1);
#pragma unroll
  for (int s = 0; s < 4; s++) ldsm4t(a[s][0], a[s][1], a[s][2], a[s][3], sa + (mi & 1) * 1024 + (mi >> 1) * 512 + s * 128 + n * 16);
  gen(2); SPLIT(2); use(0); gen(3); SPLIT(3); use(1); gen(4); midway(); use(2); gen(5); SPLIT(5); use(3); gen(6); SPLIT(6); use(4);
#undef SPLIT
  TRC(true, 46);
#pragma unroll
  for (int i = 0; i < 5; i++)
    sts128(sa + i * 512 + lane * 16, __float_as_uint(kk[i][0]), __float_as_uint(kk[i][1]), __float_as_uint(kk[i][2]), __float_as_uint(kk[i][3]));
  sts32(sa + 2560 + lane * 4, __float_as_uint(fmaf(q.r, w128.r, -q.i * w128.i)));
}

__global__ void __cluster_dims__(2, 1, 1) __launch_bounds__(NTHREADS, 1) fused_kernel(const __grid_constant__ Params prm) {
  extern __shared__ __align__(1024) uint8_t smem_raw[];
  const uint32_t sb = (uint32_t)__cvta_generic_to_shared(smem_raw);
  const uint32_t bar0 = sb + OFF_BAR;
  const int warp = __shfl_sync(0xffffffffu, threadIdx.x >> 5, 0);
  int lane = threadIdx.x & 31;
  if (lane == 0) TR2(160 + warp);
  uint8_t* const scr = prm.scr;
  const int cl = ((blockIdx.x >> 1) + 60) & 63, r7 = (cl - 32) * 37 >> 8, p7 = cl - 32 - 7 * r7;
  const int mp = cl < 32 ? cl & 7 : cl < 60 ? p7 + (p7 >= GPOS) : GPOS;
  const int rnd = cl < 32 ? cl >> 3 : cl < 60 ? r7 : cl - 60;
  const int fc = FCMAP ? 2 * rnd + (cl >> 5) : rnd + 4 * (cl >> 5), rank = blockIdx.x & 1, cb = blockIdx.x;
  uint32_t pa[7];
#pragma unroll
  for (int i = 0; i < 7; i++) {
    uint16_t v;
    const int ch = cb * 4 + ((threadIdx.x >> 5) & 3);
    asm volatile("ld.global.nc.u16 %0, [%1];" : "=h"(v) : "l"(prm.ssm[i] + (i < 6 ? ch * 128 + (threadIdx.x >> 7) * 32 + lane : ch)));
    pa[i] = v;
  }
  TRC(true, 49);
  if ((sb & 0xffffff) != SB0) asm volatile("trap;");
  if (threadIdx.x >= 448 && elect()) {
    if (threadIdx.x < 480) {
#pragma unroll
      for (int i = 0; i < 17; i++) mbar_init(bar0 + 8 * (B_F1 + i), 1);
      mbar_init(bar0 + 8 * B_KG, 16);
    } else {
#pragma unroll
      for (int i = 0; i < 18; i++) mbar_init(bar0 + 8 * (B_C1 + i), 4);
    }
    asm volatile("fence.mbarrier_init.release.cluster;" ::: "memory");
  }
  __syncwarp();
  asm volatile("barrier.cluster.arrive.relaxed.aligned;" ::: "memory");
  const int mt = 2 * mp + rank, mt2 = 2 * mp + (fc & 1), nt = (fc & 6) + rank;
  const int w = warp & 3;

  if (lane == 0) TR2(176 + warp);
  const int fa = 176 * fc + 48 * (fc & 1), fb = (fc & 1) ? 176 * fc : 176 * fc + 128;
  auto load_g1 = [&](int s, uint32_t xs) {
    const CUtensorMap* wm = rank ? &prm.wu : &prm.wg;
    const uint32_t fbar = bar0 + 8 * (B_F1 + s), dst = sb + OFF_W + (s & 3) * 24576 + rank * 12288;
    const int k0 = ((s + 2 * mp) & 15) * 32;
    mbar_expect(fbar, (s & 1) ? 24576 : 40960);
    if (!(s & 1)) tma2d(xs, &prm.x, fbar, k0, mt * 128);
    tma2d_mc(dst, wm, fbar, fa, k0);
    tma2d_mc(dst + 4096, wm, fbar, fa + 64, k0);
    tma2d_mc(dst + 8192, wm, fbar, fb, k0);
  };
  uint4 xv[8];
  {
    if (warp >= 12) {
      if (WPF && w < 2 && elect()) {
        const CUtensorMap* wm = rank ? &prm.wu : &prm.wg;
        tma2d_pf(wm, fa, mp * 64 + w * 32); tma2d_pf(wm, fa + 64, mp * 64 + w * 32); tma2d_pf(wm, fb, mp * 64 + w * 32);
      }
      __syncwarp();
      asm volatile("barrier.cluster.wait.aligned;" ::: "memory");
      if (w == 0 && lane == 0) TR2(53);
      if (w >= 2) __nanosleep(RING_NS);
      if (elect()) {
        load_g1(w, sb + OFF_X + (w >> 1) * 16384);
        if (XPF && w == 3) asm volatile("cp.async.bulk.prefetch.L2.global [%0], 16384;" ::"l"(prm.xp + (mt * 8 + fc) * 16 * D_) : "memory");
      }
      if (w == 0 && lane == 0) TR2(54);
    } else if (warp >= 8) {
      sts32(sb + OFF_STAT + lane * 4, 0x3f803f80u);
      fence_async_smem();
      if (elect()) {
#pragma unroll 1
        for (int q = 2 * w; q < 2 * w + 2; q++) {
          const int cnt = q == 0 ? 1 : q < 4 ? 2 : q < 7 ? 4 : 8;
#pragma unroll
          for (int i = 0; i < 9; i++) mbar_init(bar0 + 8 * (36 + q * 9 + i), cnt);
        }
      }
    } else {
#pragma unroll 1
      for (int i = threadIdx.x; i < 4 * TAP_CH / 16; i += 256) sts128(sb + OFF_TAP + i * 16, 0, 0, 0, 0);
      if (threadIdx.x < 48) sts128(sb + OFF_FIX + threadIdx.x * 16, 0, 0, 0, 0);
    }
    __syncwarp();
    if (warp < 12) asm volatile("barrier.cluster.wait.aligned;" ::: "memory");

    __syncwarp();
    kgen(sb, warp, lane, pa, [&]() {
      if (!XMID) { if (warp == 20) asm volatile("trap;"); }
      else if ((warp >> 2) == 2) {
        const uint4* xp = reinterpret_cast<const uint4*>(prm.xp + ((mt * 8 + fc) * 16 + (w & 1) * 8 + (lane >> 2)) * D_ + (w >> 1) * 256 + (lane & 3) * 8);
#pragma unroll
        for (int i = 0; i < 8; i++)
          asm volatile("ld.global.nc.v4.u32 {%0,%1,%2,%3}, [%4];" : "=r"(xv[i].x), "=r"(xv[i].y), "=r"(xv[i].z), "=r"(xv[i].w) : "l"(xp + i * 4) : "memory");
      }
    });
  }
  __syncwarp();
  if (lane == 0 && (!CSMODE || (warp >> 2) != 2)) mbar_arrive(bar0 + 8 * B_KG);
  if (lane == 0) TR2(224 + warp);
  int g, c, mi, n;
#define LANE_VARS() do { asm volatile("mov.u32 %0, %%laneid;" : "=r"(lane)); g = lane >> 2; c = lane & 3; mi = lane >> 3; n = lane & 7; } while (0)

  if (warp < 8) {
    asm volatile("setmaxnreg.inc.sync.aligned.u32 208;");
    LANE_VARS();
    const int wg = (warp >> 2) ^ WGSWAP;
    const bool lead = w == 0 && lane == 0;
    {
      float ag[88], au[88];
      constexpr uint32_t db0 = mkdesc(OFF_W, 4096);
      uint32_t da = mkdesc(OFF_X, 16) + wg * 512, db = db0, fbar = bar0 + 8 * B_F1, cbar;
      asm("mapa.shared::cluster.u32 %0, %1, %2;" : "=r"(cbar) : "r"(bar0 + 8 * (B_C1 - 1)), "r"(lane & 1));
      const bool sig = w == 0 && lane < 2;
      auto release = [&](int i) { if (sig) asm volatile("mbarrier.arrive.shared::cluster.b64 _, [%0];" ::"r"(cbar + 8 * i) : "memory"); };
      mbar_wait(bar0 + 8 * B_KG);
#pragma unroll 1
      for (int s = 0; s < 16; s += 2) {
#pragma unroll
        for (int k = 0; k < 2; k++) {
          mbar_wait(fbar + 8 * k);
          if (lead && (TRACE_ALL || s + k == 0)) TR(64 + wg * 16 + s + k);
          wg_fence();
          wgmma176_ss(ag, da + 4 * k, db + 1536 * k, s + k);
          wgmma176_ss(au, da + 4 * k, db + 1536 * k + 768, s + k);
          wgmma176_ss(ag, da + 4 * k + 2, db + 1536 * k + 128, 1);
          wgmma176_ss(au, da + 4 * k + 2, db + 1536 * k + 896, 1);
          wg_commit();
          wg_wait<1>();
          if (s + k > 0) release(k);
        }
        da += (s == 4 || s == 10) ? -2048 : 1024;
        db ^= 3072;
        fbar += 16; cbar += 16;
      }
      mbar_wait(bar0 + 8 * (B_F1 + 16));
      const float r0 = __uint_as_float(lds32(sb + OFF_STAT + (wg * 64 + w * 16 + g) * 4)), r1 = __uint_as_float(lds32(sb + OFF_STAT + (wg * 64 + w * 16 + g + 8) * 4));
      wg_fence();
      wgmma176_ns(ag, mkdesc(OFF_W + 2048, 0) + wg * 64, db0, 1);
      wgmma176_ns(au, mkdesc(OFF_W + 2048, 0) + wg * 64, db0 + (12288 >> 4), 1);
      wg_commit();
      wg_wait<1>();
      release(0);
      wg_wait<0>();
      release(1);
      if (lead) TR(4 + wg);
#pragma unroll
      for (int p = 0; p < 3; p++) {
        const uint32_t hs = sb + OFF_X + p * 16384 + wg * 8192 + (2 * w + (mi & 1)) * (p < 2 ? 1024 : 768) + (mi >> 1) * 128 + n * 16;
#pragma unroll
        for (int j = 8 * p; j < 8 * p + 8 && j < 22; j += 2) {
          uint32_t q[4];
#pragma unroll
          for (int i = 0; i < 4; i++) {
            const int e = 4 * j + 2 * i;
            const float r = (i & 1) ? r1 : r0;
            q[i] = pack2(ag[e] * r * au[e], ag[e + 1] * r * au[e + 1]);
          }
          stsm4(hs + (j & 7) * 128, q[0], q[1], q[2], q[3]);
        }
        fence_async_smem();
        __syncwarp();
        if (lane == 0) mbar_arrive(bar0 + 8 * (B_ST + wg * 3 + p));
      }
    }
    if (lead) TR(wg ? 36 : 6);
    const uint32_t to = ((mi >> 1) * 8 + n) * 128 + (((2 * w + (mi & 1)) ^ n) << 4);
    float acc[64];
    uint32_t ta[2][8][4], xq[32];
    const uint32_t pp = sb + OFF_TAP + 2 * wg * TAP_CH + (16 + 128 * (w & 2) + 8 * (w & 1) + g - 2 * c) * 4;
    auto load_taps = [&](int v) {
      const uint32_t a = pp + (v >> 3) * TAP_CH + (v & 7) * 64;
      ta[v >> 3][v & 7][0] = lds32(a); ta[v >> 3][v & 7][1] = lds32(a + 512);
      ta[v >> 3][v & 7][2] = lds32(a - 32); ta[v >> 3][v & 7][3] = lds32(a + 480);
    };
    auto near = [&](int i) {
      const uint32_t db = mkdesc(OFF_XT + 1024, 16) + (2 * wg + i) * 2;
      const int turn = 10 + 2 * i + wg;
      if (turn > 10) asm volatile("bar.sync %0, 256;" ::"r"(turn) : "memory");
      if (lead) TR2(208 + turn);
      wg_fence();
      wgmma128_rs<0>(acc, ta[i][0], db);
#pragma unroll
      for (int j0 = 1; j0 < 8; j0++) {
        if (j0 == PASSJ && turn < 13) asm volatile("bar.arrive %0, 256;" ::"r"(turn + 1) : "memory");
        wgmma128_rs<1>(acc, ta[i][j0], db - 8 * j0);
      }
      wg_commit();
      if (PASSJ == 8 && turn < 13) asm volatile("bar.arrive %0, 256;" ::"r"(turn + 1) : "memory");
      if (lead) TR2(202 + turn);
    };
    auto fold = [&](uint32_t (&q)[16]) {
      q[0] = pack2(acc[0], acc[1]);
#pragma unroll
      for (int p = 1; p < 16; p++) q[p] = pack2(acc[4 * p] + acc[4 * p - 2], acc[4 * p + 1] + acc[4 * p - 1]);
    };
    uint32_t ym[8], q[16], a[8];
    const uint32_t yo0 = (w & 2) * 1024 + mi * 256 + (w & 1) * 128 + ((n ^ (4 * (w & 1))) << 4);
    auto merge_a = [&](int i) {
      const uint32_t fr = sb + OFF_YS + wg * YS_STEP + i * 4096 + yo0, f = sb + OFF_MID + (2 * wg + i) * 4096 + yo0;
      ldsm4t(ym[0], ym[1], ym[2], ym[3], f);
      ldsm4t(ym[4], ym[5], ym[6], ym[7], f + 1024);
      ldsm4t(a[4], a[5], a[6], a[7], fr + 1024);
      if (w & 2) ldsm4t(a[0], a[1], a[2], a[3], fr);
      wg_wait<0>();
      if (i) {
        if (w == 0 && lane < 2) mbar_arrive(bar0 + 8 * B_CONV);
        if (lead) TR(wg ? 32 : 31);
      }
      fold(q);
    };
    auto merge_s = [&](int i) {
      const uint32_t ex = sb + OFF_TAP + (2 * wg + i) * TAP_CH + (w & 1) * 1792;
#pragma unroll
      for (int p = 4; p < 8; p++) ym[p] = hadd2(ym[p], a[p]);
      if (w & 2) {
        sts64(ex + 1536 + lane * 8, q[0], q[1]);
        sts128(ex + 1024 + lane * 16, q[2], q[3], q[4], q[5]);
#pragma unroll
        for (int p = 0; p < 8; p++) ym[p] = hadd2(p < 4 ? hadd2(ym[p], a[p]) : ym[p], q[6 + p]);
      } else {
        sts128(ex + lane * 16, q[8], q[9], q[10], q[11]);
        sts128(ex + 512 + lane * 16, q[12], q[13], q[14], q[15]);
        ym[0] = q[0]; ym[1] = q[1]; ym[2] = q[2];
#pragma unroll
        for (int p = 3; p < 8; p++) ym[p] = hadd2(ym[p], q[p]);
      }
    };
    auto merge_b = [&](int i) {
      const uint32_t ex = sb + OFF_TAP + (2 * wg + i) * TAP_CH + (w & 1) * 1792, f = sb + OFF_YS + wg * YS_STEP + i * 4096 + yo0;
      uint4 e;
      asm volatile("bar.sync %0, 64;" ::"r"(7 + 2 * wg + (w & 1)) : "memory");
      if (w & 2) e = lds128(ex + lane * 16);
      else { const uint2 v = lds64(ex + 1536 + lane * 8); e = make_uint4(0u, 0u, v.x, v.y); }
      const uint4 v = lds128(ex + ((w & 2) ? 512 : 1024) + lane * 16);
      stsm4t(f, hadd2(ym[0], e.x), hadd2(ym[1], e.y), hadd2(ym[2], e.z), hadd2(ym[3], e.w));
      stsm4t(f + 1024, hadd2(ym[4], v.x), hadd2(ym[5], v.y), hadd2(ym[6], v.z), hadd2(ym[7], v.w));
    };
    auto publish = [&](int i) {
      fence_async_smem();
      __syncwarp();
      if (lane == 0) mbar_arrive(bar0 + 8 * (B_YST + 2 * i + wg));
    };
    auto load_res = [&]() {
      mbar_wait(bar0 + 8 * B_XR);
#pragma unroll
      for (int j = 0; j < 8; j++) ldsm4t(xq[4 * j], xq[4 * j + 1], xq[4 * j + 2], xq[4 * j + 3], sb + OFF_W + 3 * 8192 + to + j * 2048);
      __syncwarp();
      if (lane == 0) mbar_arrive(bar0 + 8 * B_XRD);
    };
    if (XPOS == 3 && wg) load_res();
    mbar_wait(bar0 + 8 * B_BOX);
    mbar_wait(bar0 + 8 * B_XT);
    if (wg == 0) {
      float y[12][4];
      conv_far(sb, w, lane, y, load_taps);
      __syncwarp();
      if (lane == 0) mbar_arrive(bar0 + 8 * B_HM);
      if (lead) TR(39);
      uint32_t q[24];
#pragma unroll
      for (int e = 0; e < 24; e++) q[e] = pack2(y[e >> 1][2 * (e & 1)], y[e >> 1][2 * (e & 1) + 1]);
      mbar_wait(bar0 + 8 * B_HM);
      if (lead) TR(30);
      near(0);
      const uint32_t f = sb + OFF_YS + (w >> 1) * YS_STEP + (w & 1) * 4096 + 1024 + mi * 128 + ((n ^ (4 * (mi & 1))) << 4);
#pragma unroll
      for (int p = 0; p < 6; p++) stsm4t(f + p * 512, q[4 * p], q[4 * p + 1], q[4 * p + 2], q[4 * p + 3]);
      __syncwarp();
      if (lane == 0) mbar_arrive(bar0 + 8 * B_YP);
    } else {
      float y[13][4];
      conv_mid(sb, w, lane, y, load_taps);
      __syncwarp();
      if (lane == 0) mbar_arrive(bar0 + 8 * B_HM);
      if (lead) TR(35);
      if (XPOS == 0) load_res();
      const uint32_t f = sb + OFF_MID + w * 4096 + 1024 + (mi >> 1) * 256 + (n & 1) * 128 + (4 * ((mi ^ n) & 1) + (n >> 1)) * 16;
      mbar_wait(bar0 + 8 * B_HM);
      stsm2(f - 256, pack2(y[0][0], y[0][1]), pack2(y[0][2], y[0][3]));
#pragma unroll
      for (int p = 1; p < 13; p += 2)
        stsm4(f + (p - 1) * 256, pack2(y[p][0], y[p][1]), pack2(y[p][2], y[p][3]), pack2(y[p + 1][0], y[p + 1][1]), pack2(y[p + 1][2], y[p + 1][3]));
      __syncwarp();
      if (lane == 0) mbar_arrive(bar0 + 8 * B_YP);
      if (XPOS == 1) load_res();
      near(0);
      if (XPOS == 2) load_res();
    }
    mbar_wait(bar0 + 8 * B_YP);
    merge_a(0);
    merge_s(0);
    near(1);
    merge_b(0);
    publish(0);
    merge_a(1);
    if (!((DEFP >> wg) & 1)) { merge_s(1); merge_b(1); publish(1); }
    if (lead) TR(wg ? 38 : 47);
    const uint32_t da0 = mkdesc(OFF_W, 4096), db0 = mkdesc(OFF_X, 128);
    uint32_t da = da0 + (4 - wg) * 512, db = db0;
#pragma unroll 1
    for (int u = 0; u < 8; u++) {
      mbar_wait(bar0 + 8 * (B_F2 + u));
      if (lead && (TRACE_ALL || u == 0)) TR(144 - wg * 16 + u);
      wg_fence();
      wgmma128_t<1024>(acc, da, db, u);
      wgmma128_t<1024>(acc, da + 128, db + 16, 1);
      wgmma128_t<1024>(acc, da + 256, db + 32, 1);
      wgmma128_t<1024>(acc, da + 384, db + 48, 1);
      da += 1024;
      if (da >= da0 + 12 * 512) da -= 12 * 512;
      db = db0 + (((uint32_t)HSEQ >> (4 * u)) & 15) * 512;
      wg_commit();
      if (((DEFP >> wg) & 1) && u == 0) { merge_s(1); merge_b(1); publish(1); }
      wg_wait<1>();
      if (lead && u > 0) {
        mbar_arrive(bar0 + 8 * (B_C2 + u - 1));
        if (u == 5) mbar_arrive_cl(bar0 + 8 * B_PF, rank ^ 1);
      }
    }
    const uint32_t pbuf = sb + OFF_X + hslot(1 + w) + 12288 + lane * 16;
    if (wg == 0) {
      mbar_wait(bar0 + 8 * B_PF);
      uint32_t ra, rb;
      asm("mapa.shared::cluster.u32 %0, %1, %2;" : "=r"(ra) : "r"(pbuf), "r"(rank ^ 1));
      asm("mapa.shared::cluster.u32 %0, %1, %2;" : "=r"(rb) : "r"(bar0 + 8 * B_PART), "r"(rank ^ 1));
      wg_wait<0>();
      if (lead) { mbar_arrive(bar0 + 8 * (B_C2 + 7)); TR2(40); }
#pragma unroll
      for (int j = 0; j < 8; j++) {
        uint32_t q[4];
#pragma unroll
        for (int i = 0; i < 4; i++) {
          const int e = 4 * j + i;
          q[i] = pack2(acc[2 * e], acc[2 * e + 1]);
        }
        asm volatile("st.async.shared::cluster.mbarrier::complete_tx::bytes.v4.u32 [%0], {%1,%2,%3,%4}, [%5];"
                     ::"r"(ra + j * 512), "r"(q[0]), "r"(q[1]), "r"(q[2]), "r"(q[3]), "r"(rb) : "memory");
      }
      if (OP == 2 && w == 1) {
        bar_sync<2, 160>();
        if (elect()) {
          tma2d_st(&prm.out, sb + OFF_W + 3 * 8192, nt * 64, mt2 * 128);
          bulk_commit();
          bulk_wait_read();
        }
      }
    } else {
      uint32_t yr[32];
      uint4 pr[8];
      const uint32_t yo = sb + OFF_YS + (mi >> 1) * YS_STEP + (w * 16 + (mi & 1) * 8 + n) * 128;
#pragma unroll
      for (int u = 8; u < 16; u++) {
        mbar_wait(bar0 + 8 * (B_F2 + u));
        if (lead) TR2(128 + u);
        wg_fence();
        const uint32_t a = da0 + ((u - 1) % 12) * 512, b = db0 + hslot(u % 7) / 16;
        wgmma128_t<768>(acc, a, b, 1);
        wgmma128_t<768>(acc, a + 128, b + 16, 1);
        wgmma128_t<768>(acc, a + 256, b + 32, 1);
        wg_commit();
        if (u < 10) {
          wg_wait<1>();
          if (w == 0 && lane <= u - 8) mbar_arrive(bar0 + 8 * (B_C2 + u - 1));
        }
        if (u == YU) {
          mbar_wait(bar0 + 8 * B_Y);
          if (lead) TR2(16);
#pragma unroll
          for (int j = 0; j < 8; j++) ldsm4(yr[4 * j], yr[4 * j + 1], yr[4 * j + 2], yr[4 * j + 3], yo + ((j ^ n ^ (mi & 2) * 2) << 4));
        }
      }
      mbar_wait(bar0 + 8 * B_PART);
      if (lead) TR2(43);
#pragma unroll
      for (int j = 0; j < 8; j++) pr[j] = lds128(pbuf + j * 512);
#pragma unroll
      for (int j = 0; j < 8; j++) {
        yr[4 * j] = hadd2(hadd2(yr[4 * j], xq[4 * j]), pr[j].x); yr[4 * j + 1] = hadd2(hadd2(yr[4 * j + 1], xq[4 * j + 1]), pr[j].y);
        yr[4 * j + 2] = hadd2(hadd2(yr[4 * j + 2], xq[4 * j + 2]), pr[j].z); yr[4 * j + 3] = hadd2(hadd2(yr[4 * j + 3], xq[4 * j + 3]), pr[j].w);
      }
      wg_wait<0>();
      if (lead) TR(17);
#pragma unroll
      for (int hf = 0; hf < OP; hf++) {
#pragma unroll
        for (int j = 8 / OP * hf; j < 8 / OP * (hf + 1); j++) {
          uint32_t q[4];
#pragma unroll
          for (int i = 0; i < 4; i++) {
            const int e = 4 * j + i;
            q[i] = hadd2(pack2(acc[2 * e], acc[2 * e + 1]), yr[e]);
          }
          stsm4t(sb + OFF_W + 3 * 8192 + to + j * 2048, q[0], q[1], q[2], q[3]);
        }
        fence_async_smem();
        if (hf < OP - 1) asm volatile("bar.arrive 2, 160;" ::: "memory");
      }
      bar_sync<1>();
      if (w == 0 && elect()) {
        tma2d_st(&prm.out, sb + OFF_W + 3 * 8192 + (OP - 1) * 8192, nt * 64, mt2 * 128 + (OP - 1) * 64);
        bulk_commit();
        TR(18);
        bulk_wait_read();
        TR(19);
      }
    }
  } else if (warp < 12) {
    asm volatile("setmaxnreg.dec.sync.aligned.u32 72;");
    LANE_VARS();
    const int blk = mt * 8 + fc;
    const uint32_t TAP = sb + OFF_TAP + w * TAP_CH;
    const int th = w & 1, chh = w >> 1;
    auto load_x = [&]() {
      const uint4* xp = reinterpret_cast<const uint4*>(prm.xp + (blk * 16 + th * 8 + g) * D_ + chh * 256 + c * 8);
#pragma unroll
      for (int i = 0; i < 8; i++)
        asm volatile("ld.global.nc.v4.u32 {%0,%1,%2,%3}, [%4];" : "=r"(xv[i].x), "=r"(xv[i].y), "=r"(xv[i].z), "=r"(xv[i].w) : "l"(xp + i * 4) : "memory");
    };
    if (!XMID && !CSMODE) load_x();
    if (!CSMODE) mbar_wait(bar0 + 8 * B_KG);
    {
      float cs[3][4];
      mbar_wait(bar0 + 8 * (B_F1 + CSS));
      mbar_wait(bar0 + 8 * (B_F1 + CSS + 1));
      if (w == 0 && lane == 0) TR2(58);
      const uint32_t da = mkdesc(OFF_W + CSS * 24576, 4096) + rank * 768;
      wg_fence();
#pragma unroll
      for (int k = 0; k < 4; k++)
#pragma unroll
        for (int at = 0; at < 3; at++) wgmma8_t(cs[at], da + (k >> 1) * 1536 + (k & 1) * 128 + at * 256, mkdesc(OFF_STAT, 0), k);
      wg_commit();
      if (CSMODE && lane == 0) mbar_arrive(bar0 + 8 * B_KG);
      if (!XMID && CSMODE) load_x();
      wg_wait<0>();
      if (w == 0 && lane < 4) mbar_arrive_cl(bar0 + 8 * B_CS, lane & 1);
      if (w == 0 && lane == 0) TR2(25);
#pragma unroll
      for (int at = 0; at < 3; at++) {
        const float v = (c & 2) ? cs[at][2] : cs[at][0], vh = bf_round(v);
        sts16(sb + OFF_AUX + (c & 1) * 384 + (at * 64 + w * 16 + (c & 2) * 4 + g) * 2, pack2((c & 1) ? v - vh : vh, 0.f));
      }
    }
    {
      uint32_t z = lds32(sb + OFF_STAT) & 0x40, km = z | 0xffff0000u, ks = z | 0x10000u;
      float s0 = 0.f, s1 = 0.f;
#pragma unroll
      for (int i = 0; i < 8; i++) {
        const uint32_t u[4] = {xv[i].x, xv[i].y, xv[i].z, xv[i].w};
#pragma unroll
        for (int k = 0; k < 4; k++) { s0 += __uint_as_float(u[k] * ks); s1 += __uint_as_float(u[k] & km); }
      }
      s0 += s1;
      s0 += __shfl_xor_sync(0xffffffffu, s0, 1);
      s0 += __shfl_xor_sync(0xffffffffu, s0, 2);
      const float mh = s0 * (1.f / 256.f);
      z &= __float_as_uint(mh); km = z | 0xffff0000u; ks = z | 0x10000u;
      float q0 = 0.f, q1 = 0.f;
#pragma unroll
      for (int i = 0; i < 8; i++) {
        const uint32_t u[4] = {xv[i].x, xv[i].y, xv[i].z, xv[i].w};
#pragma unroll
        for (int k = 0; k < 4; k++) {
          const float a = __uint_as_float(u[k] * ks) - mh, b = __uint_as_float(u[k] & km) - mh;
          q0 = fmaf(a, a, q0); q1 = fmaf(b, b, q1);
        }
      }
      q0 += q1;
      q0 += __shfl_xor_sync(0xffffffffu, q0, 1);
      q0 += __shfl_xor_sync(0xffffffffu, q0, 2);
      LANE_VARS();
      if (c == 0) sts64(sb + OFF_MISC + w * 64 + g * 8, __float_as_uint(mh), __float_as_uint(q0));
      bar_sync<1>();
      if (CSMODE) mbar_wait(bar0 + 8 * B_KG);
      const uint2 o = lds64(sb + OFF_MISC + (w ^ 2) * 64 + g * 8);
      const float mo = __uint_as_float(o.x), dm = mh - mo;
      const uint32_t nm = pack2(-0.5f * (mh + mo), -0.5f * (mh + mo));
      const float var = bf_round((q0 + __uint_as_float(o.y) + dm * dm * 128.f) * (1.f / 512.f));
      float sd, r;
      asm("sqrt.approx.f32 %0, %1;" : "=f"(sd) : "f"(bf_round(var + 1e-5f)));
      asm("rcp.approx.f32 %0, %1;" : "=f"(r) : "f"(bf_round(sd)));
      if (chh == 0) sts32(sb + OFF_AUX + 768 + th * 128 + lane * 4, nm);
      else if (c == 0) sts32(sb + OFF_AUX + 1024 + th * 32 + g * 4, __float_as_uint(r * r));
      const uint32_t rh = pack2(r, r), rl = pack2(r - bf_lo(rh), r - bf_lo(rh));
      const uint32_t xs = swz(sb + OFF_XT + 1024 + (64 * chh + 2 * (n >> 1) + (mi >> 1)) * 128 + ((cpos(2 * (mi & 1) + (n & 1), th) ^ (blk & 7)) << 4));
#pragma unroll
      for (int i = 0; i < 8; i++) {
        const uint32_t u[4] = {xv[i].x, xv[i].y, xv[i].z, xv[i].w};
        uint32_t q[4];
#pragma unroll
        for (int k = 0; k < 4; k++) {
          const uint32_t dd = hadd2(u[k], nm);
          asm("{.reg .b32 t; mul.rn.bf16x2 t, %1, %3; fma.rn.bf16x2 %0, %1, %2, t;}" : "=r"(q[k]) : "r"(dd), "r"(rh), "r"(rl));
        }
        stsm4t(xs + i * 1024, q[0], q[1], q[2], q[3]);
      }
    }
    fence_async_smem();
    __syncwarp();
    LANE_VARS();
    if (lane == 0) mbar_arrive(bar0 + 8 * B_LNST);
    if (w == 0 && lane == 0) TR(24);
    {
      float kk[5][4];
      const float dsk = __bfloat162float(prm.dskip[cb * 4 + w]);
      float k2048 = 0.f;
#pragma unroll
      for (int i = 0; i < 5; i++) kk[i][0] = kk[i][1] = kk[i][2] = kk[i][3] = 0.f;
#pragma unroll 1
      for (int u = 0; u < 4; u++) {
        const uint32_t dp = sb + OFF_S + (4 * u + w) * KG_DUMP;
#pragma unroll
        for (int i = 0; i < 5; i++) {
          const uint4 v = lds128(dp + i * 512 + lane * 16);
          kk[i][0] += __uint_as_float(v.x); kk[i][1] += __uint_as_float(v.y); kk[i][2] += __uint_as_float(v.z); kk[i][3] += __uint_as_float(v.w);
        }
        k2048 += __uint_as_float(lds32(dp + 2560 + lane * 4));
      }
#pragma unroll
      for (int o = 16; o; o >>= 1) k2048 += __shfl_xor_sync(0xffffffffu, k2048, o);
      const float k512 = bf_round(__shfl_sync(0xffffffffu, kk[3][0], 0));
      if (lane == 0) kk[0][0] += dsk;
      if (lane == 31) kk[2][3] -= k512;
#pragma unroll
      for (int h = 0; h < 2; h++) {
        const int a = g + 8 * h;
#pragma unroll
        for (int i = 0; i < 2; i++) {
          const uint32_t p = pack2(kk[i][2 * h + 1], kk[i][2 * h]), ad = TAP + (16 + 128 * i + 8 * a + 2 * c) * 4;
          sts16(ad, p >> 16); sts32(ad + 4, p); sts16(ad + 10, p);
        }
        {
          const int L = 256 + 128 * (c >> 1) + 4 * (c & 1) + 8 * a;
          const uint32_t p = pack2(kk[2][2 * h + 1], kk[2][2 * h]), p0 = __byte_perm(p, p, 0x3232), ad = TAP + (16 + L) * 4;
          if (L != 256) { sts16(ad - 4, p0); sts16(ad + 2, p0); }
          sts16(ad, p0); sts32(ad + 4, p0); sts32(ad + 8, p); sts16(ad + 14, p);
        }
        {
          const uint32_t p = pack2(kk[3][2 * h], kk[3][2 * h + 1]), o = (8 + 16 * c + a) * 4;
          sts16(TAP + TAP_5 + o, p); sts16(TAP + TAP_5 + o + 6, p);
          sts16(TAP + TAP_3 + o, p >> 16); sts16(TAP + TAP_3 + o + 6, p >> 16);
        }
        {
          const uint32_t p = pack2(kk[4][2 * h], kk[4][2 * h + 1]);
          const uint32_t ad = TAP + ((a & 1) ? TAP_7 : TAP_9) + (16 + 16 * c + (a >> 1)) * 4;
          if (h == 0 && lane == 0) {
            sts16(TAP + TAP_5 + 72 * 4, p); sts16(TAP + TAP_5 + 72 * 4 + 6, p);
            const uint32_t fp = sb + OFF_FIX + w * 192 + 19 * 4;
            sts16(fp, p); sts32(fp + 4, __byte_perm(p, p, 0x1010)); sts16(fp + 10, p);
            sts16(TAP + TAP_9 + 80 * 4, pack2(k2048, 0.f));
          } else { sts16(ad, p); sts16(ad + 6, p); }
          sts16(ad + 32, p >> 16); sts16(ad + 38, p >> 16);
        }
      }
    }
    if (w == 0 && lane == 0) TR2(27);
    bar_sync<1>();
    if (lane < 16) sts128(swz(sb + OFF_XT + (lane >> 1) * 128 + cpos(w, lane & 1) * 16), 0, 0, 0, 0);
    __syncwarp();
    mbar_wait(bar0 + 8 * B_XT);
    if (w == 0 && lane == 0) TR2(28);
    {
      const uint32_t S = sb + OFF_S + w * SA_CH, SB = sb + OFF_SB + w * SB_CH, xt = sb + OFF_XT + 1024;
      if (lane < 16) sts128(lane < 7 ? S + S_5 + lane * 16 : lane == 7 ? SB + S_9 : S + S_3 + (lane - 8) * 16, 0, 0, 0, 0);
      if (lane < 8) {
        float s = 0.f;
#pragma unroll 1
        for (int t = 1526 + lane; t < 1531 + lane; t++) {
          s += bf_lo(lds16(swz(xt + (t >> 4) * 128 + cpos(w, (t >> 3) & 1) * 16) + (t & 7) * 2));
        }
        sts16(S + S_5 + 199 * 16 + lane * 2, pack2(s, 0.f));
      }
#pragma unroll 1
      for (int it = 0; it < 3; it++) {
        const int b = it * 32 + lane;
        const uint32_t a0 = swz(xt + (b - 1) * 128 + cpos(w, 0) * 16), a1 = swz(xt + b * 128 + cpos(w, 0) * 16);
        const uint2 u0 = lds64(a0 + 8);
        const uint4 u1 = lds128(a0 ^ 16), u2 = lds128(a1), u3 = lds128(a1 ^ 16);
        const uint32_t u[13] = {u0.x, u0.y, u1.x, u1.y, u1.z, u1.w, u2.x, u2.y, u2.z, u2.w, u3.x, u3.y, u3.z};
        float p[26];
        p[0] = 0.f;
#pragma unroll
        for (int i = 0; i < 25; i++) p[i + 1] = (i ? p[i] : 0.f) + ((i & 1) ? bf_hi(u[i >> 1]) : bf_lo(u[i >> 1]));
#define BOX(w, i) pack2(p[(i) + (w) + 1] - p[(i) - (w)], p[(i) + (w) + 2] - p[(i) - (w) + 1])
#define BOX8(ad, w, i) sts128(ad, BOX(w, i), BOX(w, (i) + 2), BOX(w, (i) + 4), BOX(w, (i) + 6))
        BOX8(S + S_5 + (2 * b + 7) * 16, 2, 4);
        BOX8(S + S_5 + (2 * b + 8) * 16, 2, 12);
        BOX8(S + S_3 + (2 * b + 8) * 16, 1, 8);
        BOX8(S + S_3 + (2 * b + 9) * 16, 1, 16);
        if (it < 2) {
          BOX8(SB + S_7 + b * 16, 3, 4);
          BOX8(SB + S_7 + 1024 + b * 16, 3, 12);
          BOX8(SB + S_9 + 1024 + b * 16, 4, 4);
          if (b < 63) BOX8(SB + S_9 + (b + 1) * 16, 4, 12);
        }
#undef BOX8
#undef BOX
      }
    }
    __syncwarp();
    if (lane == 0) mbar_arrive(bar0 + 8 * B_BOX);
    if (w == 0 && lane == 0) TR(29);
  } else {
    asm volatile("setmaxnreg.dec.sync.aligned.u32 24;");
    mbar_wait(bar0 + 8 * B_KG);
    LANE_VARS();
    if (w == 0) {
      uint32_t xs = sb + OFF_X + 32768;
      fence_async_smem();
#pragma unroll 1
      for (int s = 4; s < 16; s++) {
        if (s == CSS + 4) mbar_wait(bar0 + 8 * B_CS);
        mbar_wait(bar0 + 8 * (B_C1 + s - 4));
        if (lane == 0) TR2(96 + s);
        if (elect()) load_g1(s, xs);
        __syncwarp();
        if (s & 1) xs = xs == sb + OFF_X + 32768 ? sb + OFF_X : xs + 16384;
        if (lane == 0) TR2(112 + s);
      }
      mbar_wait(bar0 + 8 * B_LN);
      fence_async_gmem();
      mbar_wait(bar0 + 8 * (B_C1 + 12));
      if (elect()) {
        const uint32_t fbar = bar0 + 8 * (B_F1 + 16), dst = sb + OFF_W + rank * 12288;
        mbar_expect(fbar, 12288 + 2048 + 512);
        bulk_ld(sb + OFF_W + 2048, scr + G_NEGM + mt * 2048, 2048, fbar);
        bulk_ld(sb + OFF_STAT, scr + G_R2 + mt * 512, 512, fbar);
#pragma unroll 1
        for (int a = 0; a < 3; a++) tma2d_mc(dst + a * 4096, &prm.wext, fbar, fc * 192 + a * 64, rank * 16);
      }
      __syncwarp();
      mbar_wait(bar0 + 8 * (B_C1 + 13));
      if (elect()) {
        mbar_expect(bar0 + 8 * B_XR, 16384);
        tma2d(sb + OFF_W + 3 * 8192, &prm.x, bar0 + 8 * B_XR, nt * 64, mt2 * 128);
      }
      __syncwarp();
#pragma unroll 1
      for (int v = 0; v < 8; v++) {
        const int u = v < 5 ? v + 1 : v == 5 ? 0 : v;
        mbar_wait(bar0 + 8 * (u == 0 ? B_XRD : u < 6 ? B_C1 + 13 + ((2 * u + 1) * 11 >> 5) : B_C2 + u - 6));
        if (u == 0) fence_async_smem();
        if (elect()) {
          const int k0 = 176 * (4 * rank + (u & 3)) + 48 * (u & 1) + (u & 4) * 16;
          mbar_expect(bar0 + 8 * (B_F2 + u), 16384);
          tma2d(sb + OFF_W + (u < 5 ? 3 + 2 * u : 2 * u - 9) * 8192, &prm.w2, bar0 + 8 * (B_F2 + u), nt * 64, k0);
          tma2d(sb + OFF_W + (u < 4 ? 4 + 2 * u : 2 * u - 8) * 8192, &prm.w2, bar0 + 8 * (B_F2 + u), (nt ^ 1) * 64, k0);
        }
        __syncwarp();
        if (u == 5 && lane == 0) TR2(41);
      }
      uint32_t ws = sb + OFF_W + 7 * 8192;
#pragma unroll 1
      for (int b = 0; b < 8; b++) {
        mbar_wait(bar0 + 8 * (B_C2 + 2 + (b >> 1)));
        if (elect()) {
          mbar_expect(bar0 + 8 * (B_F2 + 8 + b), 6144);
          tma2d(ws, &prm.w2s, bar0 + 8 * (B_F2 + 8 + b), nt * 64, 176 * b + ((b & 1) ? 0 : 128));
        }
        __syncwarp();
        ws = b == 4 ? sb + OFF_W : ws + 8192;
      }
      if (elect()) {
        mbar_expect(bar0 + 8 * B_PART, 16384);
        if (OUTPF) asm volatile("prefetch.tensormap [%0];" ::"l"(&prm.out) : "memory");
      }
    } else {
      uint32_t ep;
      if (w == 1) {
        ep = ld_relaxed(scr + G_CNT + C_EP * 256) + 1;
        mbar_wait(bar0 + 8 * B_LNST);
        if (elect()) {
          const int blk = mt * 8 + fc;
#pragma unroll 1
          for (int q = 0; q < 4; q++) {
            tma2d_st(&prm.xt, sb + OFF_XT + 1024 + q * 4096, blk * 64, q * 32);
            if (q < 3) __nanosleep(XT_NS);
          }
          bulk_st(scr + G_WEXT + (rank * 16 + mp * 2) * 3072 + fc * 384, sb + OFF_AUX, 384);
          bulk_st(scr + G_WEXT + (rank * 16 + mp * 2 + 1) * 3072 + fc * 384, sb + OFF_AUX + 384, 384);
          bulk_st(scr + G_NEGM + blk * 256, sb + OFF_AUX + 768, 256);
          bulk_st(scr + G_R2 + blk * 64, sb + OFF_AUX + 1024, 64);
          bulk_commit();
          sts32(sb + OFF_MISC + 256, ep);
          bulk_wait<0>();
          TR2(26);
        }
        __syncwarp();
        if (lane < 4) signal(scr, C_LN + lane * 8 + fc);
        __syncwarp();
        if (lane == 0) TR2(56);
        if (W2PF == 1 && cb < 88 && elect()) {
          tma2d_pf(&prm.w2, (cb & 3) * 128, (cb >> 2) * 64);
          tma2d_pf(&prm.w2, (cb & 3) * 128 + 64, (cb >> 2) * 64);
        }
        __syncwarp();
        if (lane == 0) TR2(57);
        poll(scr, C_LN + (mp & 3) * 8 + n, ep * 16);
        if (elect()) {
          mbar_expect(bar0 + 8 * B_XT, 16384);
          bulk_ld(sb + OFF_XT + 1024, scr + G_XT + cb * 16384, 16384, bar0 + 8 * B_XT);
          mbar_arrive(bar0 + 8 * B_LN);
          if (cb == 0) *reinterpret_cast<uint32_t*>(scr + G_CNT + C_EP * 256) = ep;
          TR2(34);
        }
        __syncwarp();
      } else {
        if (W2PF == 2 && w == 2 && cb < 88) {
          mbar_wait(bar0 + 8 * (B_C1 + 1));
          if (elect()) {
            tma2d_pf(&prm.w2, (cb & 3) * 128, (cb >> 2) * 64);
            tma2d_pf(&prm.w2, (cb & 3) * 128 + 64, (cb >> 2) * 64);
          }
          __syncwarp();
        }
        mbar_wait(bar0 + 8 * B_LN);
        ep = lds32(sb + OFF_MISC + 256);
      }
      if (w < 3) {
        const int wg = w - 1;
        if (elect()) {
          uint8_t* hd = scr + G_H + (mt * 24 + fc) * 16384;
          const uint32_t hs = sb + OFF_X + wg * 8192, st = bar0 + 8 * (B_ST + wg * 3);
          const int cn = C_H + mt * 6 + (fc >> 2);
          mbar_wait(st);
          bulk_st(hd + wg * 8192, hs, 8192);
          bulk_commit();
          mbar_wait(st + 8);
          if (HORD) { bulk_wait<0>(); signal(scr, cn); }
          bulk_st(hd + 8 * 16384 + wg * 8192, hs + 16384, 8192);
          bulk_commit();
          if (!HORD) { bulk_wait<1>(); signal(scr, cn); }
          if (wg) TR2(20);
          bulk_wait<0>();
          signal(scr, cn + 2);
          mbar_arrive(bar0 + 8 * B_STG);
          mbar_wait(st + 16);
          if (P2LATE) mbar_wait(bar0 + 8 * B_H01);
          bulk_st(hd + 16 * 16384 + wg * 6144, hs + 32768, 6144);
          bulk_commit();
          bulk_wait<0>();
          signal(scr, cn + 4);
          mbar_arrive(bar0 + 8 * B_STG2);
          mbar_arrive(bar0 + 8 * B_STG2);
          TR2(wg ? 21 : 7);
        }
        __syncwarp();
        if (w == 1) {
          if (elect()) {
#pragma unroll 1
            for (int k = 0; k < 4; k++) {
              mbar_wait(bar0 + 8 * (B_YST + k));
              bulk_st(scr + G_YT + cb * 16384 + (2 * (k & 1) + (k >> 1)) * 4096, sb + OFF_YS + (k & 1) * YS_STEP + (k >> 1) * 4096, 4096);
            }
            bulk_commit();
            bulk_wait<0>();
            signal(scr, C_Y + (cb >> 4));
            TR2(33);
          }
          __syncwarp();
          poll(scr, C_Y + nt, ep * 16);
          if (lane == 0) TR2(37);
          if (elect()) {
            mbar_expect(bar0 + 8 * B_Y, 16384);
            tma2d(sb + OFF_YS, &prm.yt, bar0 + 8 * B_Y, mt2 * 128, nt * 64);
            tma2d(sb + OFF_YS + YS_STEP, &prm.yt, bar0 + 8 * B_Y, mt2 * 128 + 64, nt * 64);
          }
          if (lane == 0) TR2(44);
        }
      }
      if (w >= 2) {
        const uint8_t* hp = scr + G_H + mt2 * 24 * 16384;
        auto load_h = [&](int u, int sl) {
          if (lane == 0) TR2(192 + u);
          if (elect()) {
            const int bytes = u < 8 ? 16384 : 12288, i = u < 8 ? (u & 4) + 4 * rank + u : u + 8;
            mbar_expect(bar0 + 8 * (B_F2 + u), bytes);
            bulk_ld(sb + OFF_X + hslot(sl), hp + i * 16384, bytes, bar0 + 8 * (B_F2 + u));
          }
          __syncwarp();
        };
        if (w == 3) {
          mbar_wait(bar0 + 8 * (B_ST + 4));
          poll(scr, C_H + mt2 * 6 + rank, ep * 8);
          if (lane == 0) TR2(42);
          mbar_wait(bar0 + 8 * B_STG);
          if (lane == 0) TR2(192);
          if (elect()) {
#pragma unroll
            for (int u = 0; u < 2; u++) {
              mbar_expect(bar0 + 8 * (B_F2 + u), 16384);
              bulk_ld(sb + OFF_X + hslot(u), hp + (4 * rank + u) * 16384, 16384, bar0 + 8 * (B_F2 + u));
            }
            mbar_arrive(bar0 + 8 * B_H01);
          }
          __syncwarp();
          mbar_wait(bar0 + 8 * B_HM);
          fence_async_smem();
          load_h(2, 2);
          mbar_wait(bar0 + 8 * B_STG2);
          load_h(3, 3);
          mbar_wait(bar0 + 8 * B_HT);
          fence_async_gmem();
        } else {
          poll(scr, C_H + mt2 * 6 + 2 + rank, ep * 8);
          if (lane == 0) { mbar_arrive(bar0 + 8 * B_HT); TR2(45); }
          mbar_wait(bar0 + 8 * B_CONV);
          fence_async_smem();
          load_h(4, 4);
        }
        mbar_wait(bar0 + 8 * (B_YST + 2));
        mbar_wait(bar0 + 8 * (B_YST + 3));
        fence_async_smem();
        load_h(8 - w, 8 - w);
        if (w == 3) { mbar_wait(bar0 + 8 * B_C2); load_h(7, 0); }
        poll(scr, C_H + mt2 * 6 + 4 + (lane & 1), ep * 8);
#pragma unroll 1
        for (int u = 6 + w; u < 16; u += 2) {
          mbar_wait(bar0 + 8 * (B_C2 + u - 7));
          load_h(u, u - (u < 14 ? 7 : 14));
        }
      }
    }
  }
  __syncwarp();
  TREND();
}

typedef CUresult (*EncodeFn)(CUtensorMap*, CUtensorMapDataType, cuuint32_t, void*, const cuuint64_t*, const cuuint64_t*, const cuuint32_t*,
                             const cuuint32_t*, CUtensorMapInterleave, CUtensorMapSwizzle, CUtensorMapL2promotion, CUtensorMapFloatOOBfill);

void make_map(EncodeFn enc, CUtensorMap* m, const void* p, int cols, int rows, int bc, int br, bool swz) {
  cuuint64_t gd[2] = {(cuuint64_t)cols, (cuuint64_t)rows}, gs[1] = {(cuuint64_t)cols * 2};
  cuuint32_t box[2] = {(cuuint32_t)bc, (cuuint32_t)br}, es[2] = {1, 1};
  enc(m, CU_TENSOR_MAP_DATA_TYPE_BFLOAT16, 2, const_cast<void*>(p), gd, gs, box, es, CU_TENSOR_MAP_INTERLEAVE_NONE,
      swz ? CU_TENSOR_MAP_SWIZZLE_128B : CU_TENSOR_MAP_SWIZZLE_NONE, CU_TENSOR_MAP_L2_PROMOTION_L2_128B, CU_TENSOR_MAP_FLOAT_OOB_FILL_NONE);
}

}

extern "C" void kernel_launch(void* const* d_in, const int* in_sizes, int n_in, void* d_out, int out_size) {
  EncodeFn enc = nullptr;
  cudaDriverEntryPointQueryResult qr;
  cudaGetDriverEntryPoint("cuTensorMapEncodeTiled", (void**)&enc, cudaEnableDefault, &qr);
  void* scr;
  cudaGetSymbolAddress(&scr, g_scr);
  uint8_t *xt = (uint8_t*)scr + G_XT, *yt = (uint8_t*)scr + G_YT, *wext = (uint8_t*)scr + G_WEXT;
  Params p;
  make_map(enc, &p.x, d_in[0], D_, T_, 64, 128, true);
  make_map(enc, &p.wg, d_in[10], F_, D_, 64, 32, true);
  make_map(enc, &p.wu, d_in[11], F_, D_, 64, 32, true);
  make_map(enc, &p.wext, wext, 1536, 32, 64, 16, true);
  make_map(enc, &p.w2, d_in[12], D_, F_, 64, 64, true);
  make_map(enc, &p.w2s, d_in[12], D_, F_, 64, 48, true);
  make_map(enc, &p.xt, xt, 8192, 128, 64, 32, true);
  make_map(enc, &p.yt, yt, T_, D_, 64, 64, true);
  make_map(enc, &p.out, d_out, D_, T_, 64, 128 / OP, true);
  p.scr = (uint8_t*)scr;
  p.xp = (const __nv_bfloat16*)d_in[0];
  for (int i = 0; i < 7; i++) p.ssm[i] = (const __nv_bfloat16*)d_in[1 + i];
  p.dskip = (const __nv_bfloat16*)d_in[8];
  cudaFuncSetAttribute(fused_kernel, cudaFuncAttributeMaxDynamicSharedMemorySize, SMEM_BYTES);
  fused_kernel<<<128, NTHREADS, SMEM_BYTES>>>(p);
}
```

```cpp
#include <cuda_runtime.h>
#include <cuda_bf16.h>
#include <cuda.h>
#include <stdint.h>

namespace {

constexpr int T_ = 2048, D_ = 512, F_ = 1376;
constexpr int NTHREADS = 512;

constexpr uint32_t OFF_W = 0;
constexpr uint32_t OFF_X = 98304;
constexpr uint32_t OFF_S = 147456;
constexpr uint32_t SA_CH = 6400, S_5 = 0, S_3 = 3200, OFF_SB = OFF_S + 4 * SA_CH, SB_CH = 4096, S_9 = 0, S_7 = 2048;
constexpr uint32_t KG_DUMP = 2688;
constexpr uint32_t OFF_XT = 189440;
constexpr uint32_t OFF_TAP = 206848;
constexpr uint32_t TAP_CH = 3584, TAP_5 = 2176, TAP_3 = 2528, TAP_9 = 2880, TAP_7 = 3232;
constexpr uint32_t OFF_FIX = 229376;
constexpr uint32_t OFF_AUX = 221184, OFF_LNO = OFF_AUX + 4096;
constexpr uint32_t OFF_YS = 180224, YS_STEP = OFF_AUX - OFF_YS;
constexpr uint32_t OFF_MID = OFF_S;
constexpr uint64_t H_HOME0 = 0x1832242e20281c18ull, H_HOME1 = 0x063225222e1f291cull;
constexpr uint32_t H_GATE = 0x66554321;
__host__ __device__ constexpr uint32_t hhome(int u) { return (uint32_t)((u < 8 ? H_HOME0 : H_HOME1) >> (8 * (u & 7)) & 255) * 4096; }
constexpr uint32_t OFF_STAT = 230144;
constexpr uint32_t OFF_MISC = 230656;
constexpr uint32_t OFF_BAR = 230976;
constexpr uint32_t SMEM_BYTES = OFF_BAR + 896 + 512;
constexpr int B_F1 = 0, B_XT = 17, B_XL = 85,
              B_LN = 18, B_KG = 19,
              B_C1 = 20, B_CS = 37, B_BOX = 38, B_LNST = 39;
constexpr int B_Y = 40, B_XR = 41, B_PART = 42, B_HT = 43, B_STG = 44,
              B_F2 = 47, B_C2 = 63, B_PF = 71, B_CONV = 72,
              B_XRD = 73, B_YST = 74,
              B_HM = 78, B_YP = 79, B_ST = 80, B_END = 83;

constexpr size_t G_XT = 0;
constexpr size_t G_YT = G_XT + 2 * D_ * T_;
constexpr size_t G_H = G_YT + 2 * D_ * T_;
constexpr size_t G_WEXT = G_H + 16 * 24 * 16384;
constexpr size_t G_NEGM = G_WEXT + 32 * 1536 * 2;
constexpr size_t G_R2 = G_NEGM + T_ * 16;
constexpr size_t G_CNT = G_R2 + T_ * 4;
constexpr int C_LN = 0, C_H = 32, C_Y = 128, C_EP = 136;
__device__ __align__(1024) uint8_t g_scr[G_CNT + 137 * 256];
constexpr bool TRACE_ALL = false;
#define TR(i) do {} while (0)
#define TR2(i) do {} while (0)
#define TRC(c, i) do {} while (0)
#define TREND() do {} while (0)

struct Params {
  const __nv_bfloat16 *ssm[7], *w1[2], *xp, *dskip;
  uint8_t* scr;
  CUtensorMap x, wg, wu, wext, w2, w2s, xt, yt, out, xln;
};

constexpr int SPIN_LIMIT = 1 << 13;
#define RING_NS 150
#define WGSWAP 0
#define PASSJ 8
#define OP 2
#define CSMODE 1
constexpr int CSS = CSMODE ? 0 : 2;
#define GFENCE 1
#define OUTPF 1
#define GPOS 0
#define FCMAP 1
#define PU 14
#define KGK 2
#define MIDW 1
#define XEARLY 0
#define R2LATE 0
#define IFENCE 3
#define L2H ".L2::256B"
#define TPF 0
#define XPF 1
#define SPLM 0
#define REL6 0
#define YN 2
#define YU 10
#define XT_NS 30
#define POLL_NS 20

__device__ __forceinline__ void mbar_init(uint32_t b, int c) { asm volatile("mbarrier.init.shared::cta.b64 [%0], %1;" ::"r"(b), "r"(c) : "memory"); }
__device__ __forceinline__ void mbar_expect(uint32_t b, int bytes) { asm volatile("mbarrier.arrive.expect_tx.shared::cta.b64 _, [%0], %1;" ::"r"(b), "r"(bytes) : "memory"); }
__device__ __forceinline__ void mbar_arrive(uint32_t b) { asm volatile("mbarrier.arrive.shared::cta.b64 _, [%0];" ::"r"(b) : "memory"); }
__device__ __forceinline__ void mbar_arrive_cl(uint32_t b, uint32_t cta) {
  asm volatile("{.reg .b32 r; mapa.shared::cluster.u32 r, %0, %1; mbarrier.arrive.shared::cluster.b64 _, [r];}" ::"r"(b), "r"(cta) : "memory");
}
__device__ __forceinline__ void mbar_wait(uint32_t b) {
  asm volatile(
      "{.reg .pred p, q; .reg .u32 n; mov.u32 n, 0;\n"
      "W: mbarrier.try_wait.parity.shared::cta.b64 p, [%0], 0;\n"
      "add.u32 n, n, 1; setp.lt.and.u32 q, n, %1, !p;\n"
      "@q bra W;}" ::"r"(b), "n"(SPIN_LIMIT) : "memory");
}
__device__ __forceinline__ bool elect() {
  uint32_t e;
  asm volatile("{.reg .pred p; elect.sync _|p, 0xffffffff; selp.u32 %0, 1, 0, p;}" : "=r"(e));
  return e;
}
__device__ __forceinline__ void tma2d(uint32_t dst, const CUtensorMap* tm, uint32_t bar, int c0, int c1) {
  asm volatile("cp.async.bulk.tensor.2d.shared::cluster.global.mbarrier::complete_tx::bytes [%0], [%1, {%3,%4}], [%2];"
               ::"r"(dst), "l"(tm), "r"(bar), "r"(c0), "r"(c1) : "memory");
}
__device__ __forceinline__ void tma2d_mc(uint32_t dst, const CUtensorMap* tm, uint32_t bar, int c0, int c1) {
  asm volatile("cp.async.bulk.tensor.2d.shared::cluster.global.mbarrier::complete_tx::bytes.multicast::cluster [%0], [%1, {%3,%4}], [%2], %5;"
               ::"r"(dst), "l"(tm), "r"(bar), "r"(c0), "r"(c1), "h"((uint16_t)3) : "memory");
}
__device__ __forceinline__ void tma2d_st(const CUtensorMap* tm, uint32_t src, int c0, int c1) {
  asm volatile("cp.async.bulk.tensor.2d.global.shared::cta.bulk_group [%0, {%2,%3}], [%1];" ::"l"(tm), "r"(src), "r"(c0), "r"(c1) : "memory");
}
__device__ __forceinline__ void tma2d_pf(const CUtensorMap* tm, int c0, int c1) {
  asm volatile("cp.async.bulk.prefetch.tensor.2d.L2.global [%0, {%1,%2}];" ::"l"(tm), "r"(c0), "r"(c1) : "memory");
}
__device__ __forceinline__ void bulk_ld(uint32_t dst, const void* src, int bytes, uint32_t bar) {
  asm volatile("cp.async.bulk.shared::cluster.global.mbarrier::complete_tx::bytes [%0], [%1], %2, [%3];" ::"r"(dst), "l"(src), "r"(bytes), "r"(bar) : "memory");
}
__device__ __forceinline__ void bulk_st(void* dst, uint32_t src, int bytes) {
  asm volatile("cp.async.bulk.global.shared::cta.bulk_group [%0], [%1], %2;" ::"l"(dst), "r"(src), "r"(bytes) : "memory");
}
__device__ __forceinline__ void bulk_commit() { asm volatile("cp.async.bulk.commit_group;" ::: "memory"); }
__device__ __forceinline__ void bulk_wait_read() { asm volatile("cp.async.bulk.wait_group.read 0;" ::: "memory"); }
template <int N> __device__ __forceinline__ void bulk_wait() { asm volatile("cp.async.bulk.wait_group %0;" ::"n"(N) : "memory"); }
__device__ __forceinline__ void fence_async_smem() { asm volatile("fence.proxy.async.shared::cta;" ::: "memory"); }
__device__ __forceinline__ void fence_async_gmem() { if (GFENCE) asm volatile("fence.proxy.async.global;" ::: "memory"); }
template <int ID, int N = 128> __device__ __forceinline__ void bar_sync() { asm volatile("bar.sync %0, %1;" ::"n"(ID), "n"(N) : "memory"); }
__device__ __forceinline__ void signal(uint8_t* scr, int cnt) {
  asm volatile("red.relaxed.gpu.global.add.u32 [%0], 1;" ::"l"(scr + G_CNT + cnt * 256) : "memory");
}
__device__ __forceinline__ uint32_t ld_relaxed(const void* p) {
  uint32_t v;
  asm volatile("ld.relaxed.gpu.global.u32 %0, [%1];" : "=r"(v) : "l"(p) : "memory");
  return v;
}
__device__ __forceinline__ void poll(const uint8_t* scr, int cnt, uint32_t target) {
#pragma unroll 1
  for (int it = 0; it < SPIN_LIMIT * 4; it++) {
    if (__all_sync(0xffffffffu, (int)(ld_relaxed(scr + G_CNT + cnt * 256) - target) >= 0)) break;
    __nanosleep(POLL_NS);
  }
  asm volatile("fence.acquire.gpu;" ::: "memory");
  fence_async_gmem();
}
__device__ __forceinline__ void wg_fence() { asm volatile("wgmma.fence.sync.aligned;" ::: "memory"); }
__device__ __forceinline__ void wg_commit() { asm volatile("wgmma.commit_group.sync.aligned;" ::: "memory"); }
template <int N> __device__ __forceinline__ void wg_wait() { asm volatile("wgmma.wait_group.sync.aligned %0;" ::"n"(N) : "memory"); }
constexpr uint32_t SB0 = 1024;
__device__ __forceinline__ constexpr uint32_t mkdesc(uint32_t off, uint32_t lbo) { return ((SB0 + off) >> 4) | ((lbo >> 4) << 16); }
__device__ __forceinline__ void wgmma176_ss(float (&d)[88], uint32_t da, uint32_t db, int acc) {
  asm volatile("{.reg .pred p; .reg .b64 a, b; setp.ne.b32 p, %90, 0; mov.b64 a, {%88, 0x40000040}; mov.b64 b, {%89, 0x40000040};\n"
    "wgmma.mma_async.sync.aligned.m64n176k16.f32.bf16.bf16 {%0,%1,%2,%3,%4,%5,%6,%7,%8,%9,%10,%11,%12,%13,%14,%15,%16,%17,%18,%19,%20,%21,%22,%23,%24,%25,%26,%27,%28,%29,%30,%31,%32,%33,%34,%35,%36,%37,%38,%39,%40,%41,%42,%43,%44,%45,%46,%47,%48,%49,%50,%51,%52,%53,%54,%55,%56,%57,%58,%59,%60,%61,%62,%63,%64,%65,%66,%67,%68,%69,%70,%71,%72,%73,%74,%75,%76,%77,%78,%79,%80,%81,%82,%83,%84,%85,%86,%87}, a, b, p, 1, 1, 0, 1;}\n"
    : "+f"(d[0]),"+f"(d[1]),"+f"(d[2]),"+f"(d[3]),"+f"(d[4]),"+f"(d[5]),"+f"(d[6]),"+f"(d[7]),"+f"(d[8]),"+f"(d[9]),"+f"(d[10]),"+f"(d[11]),"+f"(d[12]),"+f"(d[13]),"+f"(d[14]),"+f"(d[15]),"+f"(d[16]),"+f"(d[17]),"+f"(d[18]),"+f"(d[19]),"+f"(d[20]),"+f"(d[21]),"+f"(d[22]),"+f"(d[23]),"+f"(d[24]),"+f"(d[25]),"+f"(d[26]),"+f"(d[27]),"+f"(d[28]),"+f"(d[29]),"+f"(d[30]),"+f"(d[31]),"+f"(d[32]),"+f"(d[33]),"+f"(d[34]),"+f"(d[35]),"+f"(d[36]),"+f"(d[37]),"+f"(d[38]),"+f"(d[39]),"+f"(d[40]),"+f"(d[41]),"+f"(d[42]),"+f"(d[43]),"+f"(d[44]),"+f"(d[45]),"+f"(d[46]),"+f"(d[47]),"+f"(d[48]),"+f"(d[49]),"+f"(d[50]),"+f"(d[51]),"+f"(d[52]),"+f"(d[53]),"+f"(d[54]),"+f"(d[55]),"+f"(d[56]),"+f"(d[57]),"+f"(d[58]),"+f"(d[59]),"+f"(d[60]),"+f"(d[61]),"+f"(d[62]),"+f"(d[63]),"+f"(d[64]),"+f"(d[65]),"+f"(d[66]),"+f"(d[67]),"+f"(d[68]),"+f"(d[69]),"+f"(d[70]),"+f"(d[71]),"+f"(d[72]),"+f"(d[73]),"+f"(d[74]),"+f"(d[75]),"+f"(d[76]),"+f"(d[77]),"+f"(d[78]),"+f"(d[79]),"+f"(d[80]),"+f"(d[81]),"+f"(d[82]),"+f"(d[83]),"+f"(d[84]),"+f"(d[85]),"+f"(d[86]),"+f"(d[87])
    : "r"(da), "r"(db), "r"(acc));
}
__device__ __forceinline__ void wgmma176_ns(float (&d)[88], uint32_t da, uint32_t db, int acc) {
  asm volatile("{.reg .pred p; .reg .b64 a, b; setp.ne.b32 p, %90, 0; mov.b64 a, {%88, 0x00000008}; mov.b64 b, {%89, 0x40000040};\n"
    "wgmma.mma_async.sync.aligned.m64n176k16.f32.bf16.bf16 {%0,%1,%2,%3,%4,%5,%6,%7,%8,%9,%10,%11,%12,%13,%14,%15,%16,%17,%18,%19,%20,%21,%22,%23,%24,%25,%26,%27,%28,%29,%30,%31,%32,%33,%34,%35,%36,%37,%38,%39,%40,%41,%42,%43,%44,%45,%46,%47,%48,%49,%50,%51,%52,%53,%54,%55,%56,%57,%58,%59,%60,%61,%62,%63,%64,%65,%66,%67,%68,%69,%70,%71,%72,%73,%74,%75,%76,%77,%78,%79,%80,%81,%82,%83,%84,%85,%86,%87}, a, b, p, 1, 1, 0, 1;}\n"
    : "+f"(d[0]),"+f"(d[1]),"+f"(d[2]),"+f"(d[3]),"+f"(d[4]),"+f"(d[5]),"+f"(d[6]),"+f"(d[7]),"+f"(d[8]),"+f"(d[9]),"+f"(d[10]),"+f"(d[11]),"+f"(d[12]),"+f"(d[13]),"+f"(d[14]),"+f"(d[15]),"+f"(d[16]),"+f"(d[17]),"+f"(d[18]),"+f"(d[19]),"+f"(d[20]),"+f"(d[21]),"+f"(d[22]),"+f"(d[23]),"+f"(d[24]),"+f"(d[25]),"+f"(d[26]),"+f"(d[27]),"+f"(d[28]),"+f"(d[29]),"+f"(d[30]),"+f"(d[31]),"+f"(d[32]),"+f"(d[33]),"+f"(d[34]),"+f"(d[35]),"+f"(d[36]),"+f"(d[37]),"+f"(d[38]),"+f"(d[39]),"+f"(d[40]),"+f"(d[41]),"+f"(d[42]),"+f"(d[43]),"+f"(d[44]),"+f"(d[45]),"+f"(d[46]),"+f"(d[47]),"+f"(d[48]),"+f"(d[49]),"+f"(d[50]),"+f"(d[51]),"+f"(d[52]),"+f"(d[53]),"+f"(d[54]),"+f"(d[55]),"+f"(d[56]),"+f"(d[57]),"+f"(d[58]),"+f"(d[59]),"+f"(d[60]),"+f"(d[61]),"+f"(d[62]),"+f"(d[63]),"+f"(d[64]),"+f"(d[65]),"+f"(d[66]),"+f"(d[67]),"+f"(d[68]),"+f"(d[69]),"+f"(d[70]),"+f"(d[71]),"+f"(d[72]),"+f"(d[73]),"+f"(d[74]),"+f"(d[75]),"+f"(d[76]),"+f"(d[77]),"+f"(d[78]),"+f"(d[79]),"+f"(d[80]),"+f"(d[81]),"+f"(d[82]),"+f"(d[83]),"+f"(d[84]),"+f"(d[85]),"+f"(d[86]),"+f"(d[87])
    : "r"(da), "r"(db), "r"(acc));
}
template <int SBO> __device__ __forceinline__ void wgmma128_t(float (&d)[64], uint32_t da, uint32_t db, int acc) {
  asm volatile("{.reg .pred p; .reg .b64 a, b; setp.ne.b32 p, %66, 0; mov.b64 a, {%64, 0x40000040}; mov.b64 b, {%65, %67};\n"
    "wgmma.mma_async.sync.aligned.m64n128k16.f32.bf16.bf16 {%0,%1,%2,%3,%4,%5,%6,%7,%8,%9,%10,%11,%12,%13,%14,%15,%16,%17,%18,%19,%20,%21,%22,%23,%24,%25,%26,%27,%28,%29,%30,%31,%32,%33,%34,%35,%36,%37,%38,%39,%40,%41,%42,%43,%44,%45,%46,%47,%48,%49,%50,%51,%52,%53,%54,%55,%56,%57,%58,%59,%60,%61,%62,%63}, a, b, p, 1, 1, 1, 0;}\n"
    : "+f"(d[0]),"+f"(d[1]),"+f"(d[2]),"+f"(d[3]),"+f"(d[4]),"+f"(d[5]),"+f"(d[6]),"+f"(d[7]),"+f"(d[8]),"+f"(d[9]),"+f"(d[10]),"+f"(d[11]),"+f"(d[12]),"+f"(d[13]),"+f"(d[14]),"+f"(d[15]),"+f"(d[16]),"+f"(d[17]),"+f"(d[18]),"+f"(d[19]),"+f"(d[20]),"+f"(d[21]),"+f"(d[22]),"+f"(d[23]),"+f"(d[24]),"+f"(d[25]),"+f"(d[26]),"+f"(d[27]),"+f"(d[28]),"+f"(d[29]),"+f"(d[30]),"+f"(d[31]),"+f"(d[32]),"+f"(d[33]),"+f"(d[34]),"+f"(d[35]),"+f"(d[36]),"+f"(d[37]),"+f"(d[38]),"+f"(d[39]),"+f"(d[40]),"+f"(d[41]),"+f"(d[42]),"+f"(d[43]),"+f"(d[44]),"+f"(d[45]),"+f"(d[46]),"+f"(d[47]),"+f"(d[48]),"+f"(d[49]),"+f"(d[50]),"+f"(d[51]),"+f"(d[52]),"+f"(d[53]),"+f"(d[54]),"+f"(d[55]),"+f"(d[56]),"+f"(d[57]),"+f"(d[58]),"+f"(d[59]),"+f"(d[60]),"+f"(d[61]),"+f"(d[62]),"+f"(d[63])
    : "r"(da), "r"(db), "r"(acc), "n"(SBO >> 4));
}
__device__ __forceinline__ void wgmma8_t(float (&d)[4], uint32_t da, uint32_t db, int acc) {
  asm volatile("{.reg .pred p; .reg .b64 a, b; setp.ne.b32 p, %6, 0; mov.b64 a, {%4, 0x40000040}; mov.b64 b, {%5, 0x00000008};\n"
    "wgmma.mma_async.sync.aligned.m64n8k16.f32.bf16.bf16 {%0,%1,%2,%3}, a, b, p, 1, 1, 1, 0;}\n"
    : "+f"(d[0]),"+f"(d[1]),"+f"(d[2]),"+f"(d[3])
    : "r"(da), "r"(db), "r"(acc));
}
template <int ACC> __device__ __forceinline__ void wgmma128_rs(float (&d)[64], const uint32_t (&a)[4], uint32_t db) {
  asm volatile("{.reg .b64 b; mov.b64 b, {%68, 0x40000040};\n"
    "wgmma.mma_async.sync.aligned.m64n128k16.f32.bf16.bf16 {%0,%1,%2,%3,%4,%5,%6,%7,%8,%9,%10,%11,%12,%13,%14,%15,%16,%17,%18,%19,%20,%21,%22,%23,%24,%25,%26,%27,%28,%29,%30,%31,%32,%33,%34,%35,%36,%37,%38,%39,%40,%41,%42,%43,%44,%45,%46,%47,%48,%49,%50,%51,%52,%53,%54,%55,%56,%57,%58,%59,%60,%61,%62,%63}, {%64,%65,%66,%67}, b, %69, 1, 1, 0;}\n"
    : "+f"(d[0]),"+f"(d[1]),"+f"(d[2]),"+f"(d[3]),"+f"(d[4]),"+f"(d[5]),"+f"(d[6]),"+f"(d[7]),"+f"(d[8]),"+f"(d[9]),"+f"(d[10]),"+f"(d[11]),"+f"(d[12]),"+f"(d[13]),"+f"(d[14]),"+f"(d[15]),"+f"(d[16]),"+f"(d[17]),"+f"(d[18]),"+f"(d[19]),"+f"(d[20]),"+f"(d[21]),"+f"(d[22]),"+f"(d[23]),"+f"(d[24]),"+f"(d[25]),"+f"(d[26]),"+f"(d[27]),"+f"(d[28]),"+f"(d[29]),"+f"(d[30]),"+f"(d[31]),"+f"(d[32]),"+f"(d[33]),"+f"(d[34]),"+f"(d[35]),"+f"(d[36]),"+f"(d[37]),"+f"(d[38]),"+f"(d[39]),"+f"(d[40]),"+f"(d[41]),"+f"(d[42]),"+f"(d[43]),"+f"(d[44]),"+f"(d[45]),"+f"(d[46]),"+f"(d[47]),"+f"(d[48]),"+f"(d[49]),"+f"(d[50]),"+f"(d[51]),"+f"(d[52]),"+f"(d[53]),"+f"(d[54]),"+f"(d[55]),"+f"(d[56]),"+f"(d[57]),"+f"(d[58]),"+f"(d[59]),"+f"(d[60]),"+f"(d[61]),"+f"(d[62]),"+f"(d[63])
    : "r"(a[0]), "r"(a[1]), "r"(a[2]), "r"(a[3]), "r"(db), "n"(ACC));
}

__device__ __forceinline__ void mma16816(float (&d)[4], uint32_t a0, uint32_t a1, uint32_t a2, uint32_t a3, uint32_t b0, uint32_t b1) {
  asm volatile("mma.sync.aligned.m16n8k16.row.col.f32.bf16.bf16.f32 {%0,%1,%2,%3}, {%4,%5,%6,%7}, {%8,%9}, {%0,%1,%2,%3};"
               : "+f"(d[0]), "+f"(d[1]), "+f"(d[2]), "+f"(d[3]) : "r"(a0), "r"(a1), "r"(a2), "r"(a3), "r"(b0), "r"(b1));
}
__device__ __forceinline__ void ldsm4(uint32_t& r0, uint32_t& r1, uint32_t& r2, uint32_t& r3, uint32_t a) {
  asm volatile("ldmatrix.sync.aligned.m8n8.x4.shared.b16 {%0,%1,%2,%3}, [%4];" : "=r"(r0), "=r"(r1), "=r"(r2), "=r"(r3) : "r"(a) : "memory");
}
__device__ __forceinline__ void ldsm4t(uint32_t& r0, uint32_t& r1, uint32_t& r2, uint32_t& r3, uint32_t a) {
  asm volatile("ldmatrix.sync.aligned.m8n8.x4.trans.shared.b16 {%0,%1,%2,%3}, [%4];" : "=r"(r0), "=r"(r1), "=r"(r2), "=r"(r3) : "r"(a) : "memory");
}
__device__ __forceinline__ void ldsm2t(uint32_t& r0, uint32_t& r1, uint32_t a) {
  asm volatile("ldmatrix.sync.aligned.m8n8.x2.trans.shared.b16 {%0,%1}, [%2];" : "=r"(r0), "=r"(r1) : "r"(a) : "memory");
}
__device__ __forceinline__ void stsm2(uint32_t a, uint32_t r0, uint32_t r1) {
  asm volatile("stmatrix.sync.aligned.m8n8.x2.shared.b16 [%0], {%1,%2};" ::"r"(a), "r"(r0), "r"(r1) : "memory");
}
__device__ __forceinline__ void stsm4(uint32_t a, uint32_t r0, uint32_t r1, uint32_t r2, uint32_t r3) {
  asm volatile("stmatrix.sync.aligned.m8n8.x4.shared.b16 [%0], {%1,%2,%3,%4};" ::"r"(a), "r"(r0), "r"(r1), "r"(r2), "r"(r3) : "memory");
}
__device__ __forceinline__ void stsm4t(uint32_t a, uint32_t r0, uint32_t r1, uint32_t r2, uint32_t r3) {
  asm volatile("stmatrix.sync.aligned.m8n8.x4.trans.shared.b16 [%0], {%1,%2,%3,%4};" ::"r"(a), "r"(r0), "r"(r1), "r"(r2), "r"(r3) : "memory");
}
__device__ __forceinline__ uint32_t lds32(uint32_t a) { uint32_t v; asm volatile("ld.shared.u32 %0, [%1];" : "=r"(v) : "r"(a) : "memory"); return v; }
__device__ __forceinline__ uint32_t lds16(uint32_t a) { uint16_t v; asm volatile("ld.shared.u16 %0, [%1];" : "=h"(v) : "r"(a) : "memory"); return v; }
__device__ __forceinline__ uint2 lds64(uint32_t a) { uint2 v; asm volatile("ld.shared.v2.u32 {%0,%1}, [%2];" : "=r"(v.x), "=r"(v.y) : "r"(a) : "memory"); return v; }
__device__ __forceinline__ uint4 lds128(uint32_t a) { uint4 v; asm volatile("ld.shared.v4.u32 {%0,%1,%2,%3}, [%4];" : "=r"(v.x), "=r"(v.y), "=r"(v.z), "=r"(v.w) : "r"(a) : "memory"); return v; }
__device__ __forceinline__ void sts16(uint32_t a, uint32_t v) { asm volatile("st.shared.u16 [%0], %1;" ::"r"(a), "h"((uint16_t)v) : "memory"); }
__device__ __forceinline__ void sts32(uint32_t a, uint32_t v) { asm volatile("st.shared.u32 [%0], %1;" ::"r"(a), "r"(v) : "memory"); }
__device__ __forceinline__ void sts64(uint32_t a, uint32_t x, uint32_t y) { asm volatile("st.shared.v2.u32 [%0], {%1,%2};" ::"r"(a), "r"(x), "r"(y) : "memory"); }
__device__ __forceinline__ void sts128(uint32_t a, uint32_t x, uint32_t y, uint32_t z, uint32_t w) {
  asm volatile("st.shared.v4.u32 [%0], {%1,%2,%3,%4};" ::"r"(a), "r"(x), "r"(y), "r"(z), "r"(w) : "memory");
}
__device__ __forceinline__ uint32_t pack2(float lo, float hi) { uint32_t r; asm("cvt.rn.bf16x2.f32 %0, %1, %2;" : "=r"(r) : "f"(hi), "f"(lo)); return r; }
__device__ __forceinline__ uint32_t hadd2(uint32_t a, uint32_t b) { uint32_t r; asm("add.rn.bf16x2 %0, %1, %2;" : "=r"(r) : "r"(a), "r"(b)); return r; }
__device__ __forceinline__ float bf_lo(uint32_t v) { return __uint_as_float(v << 16); }
__device__ __forceinline__ float bf_hi(uint32_t v) { return __uint_as_float(v & 0xffff0000u); }
__device__ __forceinline__ float bf_round(float v) { return bf_lo(pack2(v, 0.f)); }
__device__ __forceinline__ uint32_t swz(uint32_t a) { return a ^ ((a >> 3) & 0x70); }
__device__ __forceinline__ int cpos(int ch, int half) { return 2 * ch + half; }

__device__ __forceinline__ int col_a(int f) { return __byte_perm(0x120b0700, 0x27201c17, f | 0x4440) % 256 * 32; }
__device__ __forceinline__ int col_b(int f) { return __byte_perm(0x211e0b08, 0x4b48352b, f | 0x4440) % 256 * 16; }

struct cf { float r, i; };
__device__ __forceinline__ cf cmul(cf a, cf b) { return cf{fmaf(-a.i, b.i, a.r * b.r), fmaf(a.i, b.r, a.r * b.i)}; }
__device__ __forceinline__ cf csq(cf a) { return cf{fmaf(a.r, a.r, -a.i * a.i), __fmul_rn(__fmul_rn(a.r, a.i), 2.f)}; }
__device__ __forceinline__ cf cexp_pow2(float zl, float hi, float lo, float e) {
  float h = hi * e;
  float f = fmaf(lo, e, h - rintf(h)) * 6.283185307179586f;
  float m;
  asm("ex2.approx.ftz.f32 %0, %1;" : "=f"(m) : "f"(zl * e));
  return cf{m * __cosf(f), m * __sinf(f)};
}

template <class F> __device__ __forceinline__ void conv_mid(uint32_t sb, int ch, int lane, float (&r)[13][4], F side) {
  const int g = lane >> 2, c = lane & 3;
  const uint32_t S = sb + OFF_S + ch * SA_CH, TAP = sb + OFF_TAP + ch * TAP_CH, tp = TAP + (g - 2 * c) * 4;
  const uint32_t z0 = lds32(TAP);
#pragma unroll
  for (int p = 0; p < 13; p++) r[p][0] = r[p][1] = r[p][2] = r[p][3] = 0.f;
#pragma unroll
  for (int cls = 0; cls < 2; cls++) {
    uint32_t x[13][2];
#pragma unroll
    for (int p = 0; p < 12; p += 2) ldsm4t(x[p + 1][0], x[p + 1][1], x[p + 2][0], x[p + 2][1], S + (cls ? S_3 : S_5) + 128 + p * 256 + ((lane ^ (~lane >> 3 & 1)) << 4));
    if (cls == 0) ldsm2t(x[0][0], x[0][1], S + ((lane & 8) ? S_5 : S_3) + (lane & 7) * 16);
    uint32_t a1 = z0;
#pragma unroll
    for (int m = 4; m <= 8; m++) {
      const uint32_t a2 = a1 + z0, a0 = lds32(tp + (cls ? TAP_3 : TAP_5) + (2 * m - 7) * 32), a3 = a0 + z0;
      a1 = lds32(tp + (cls ? TAP_3 : TAP_5) + (2 * m - 6) * 32);
      if (m < 8) { side(cls * 8 + 2 * (m - 4)); side(cls * 8 + 2 * (m - 4) + 1); }
#pragma unroll
      for (int pm = cls - 1; pm + m < 16; pm++) mma16816(r[m + pm - 3], a0, a1, a2, a3, x[pm + 1][0], x[pm + 1][1]);
    }
  }
}
template <class F> __device__ __forceinline__ void conv_far(uint32_t sb, int ch, int lane, float (&acc)[12][4], F side) {
  const int g = lane >> 2, c = lane & 3, mi = lane >> 3, n = lane & 7;
  const uint32_t S = sb + OFF_SB + ch * SB_CH, TAP = sb + OFF_TAP + ch * TAP_CH;
  const uint32_t z0 = lds32(TAP);
#pragma unroll
  for (int p = 0; p < 12; p++) acc[p][0] = acc[p][1] = acc[p][2] = acc[p][3] = 0.f;
#pragma unroll
  for (int cls = 0; cls < 2; cls++) {
    const uint32_t tp = TAP + TAP_9 + 4 + cls * (TAP_7 - TAP_9 - 4) + (g - 2 * c + 8) * 4;
    uint32_t u[8][2];
    u[0][1] = lds32(tp);
#pragma unroll
    for (int i = 0; i < 8; i++) { u[i][0] = lds32(tp + i * 32 + 32); if (i < 7) u[i + 1][1] = u[i][0] + z0; }
    const uint32_t sp = S + S_9 + cls * (S_7 - S_9) + (mi & 1) * 1024 + (mi >> 1) * 128 + n * 16;
#pragma unroll
    for (int s = 0; s < 4; s++) {
      uint32_t a0, a1, a2, a3;
      ldsm4t(a0, a1, a2, a3, sp + s * 256);
      side(cls * 4 + s);
#pragma unroll
      for (int p = 2 * s; p < 8; p++) mma16816(acc[4 + p], a0, a1, a2, a3, u[p - 2 * s][0], u[p - 2 * s][1]);
    }
  }
  const uint32_t pp = TAP + (16 + 512 + g - 2 * c) * 4, fp = sb + OFF_FIX + ch * 192 + (g - 2 * c + 16) * 4;
  const uint32_t xl = sb + OFF_XT + 1024 + (8 * (mi >> 1) + n) * 128 + cpos(ch, mi & 1) * 16, xa = swz(xl), xb = swz(xl - 128);
  const uint32_t a0 = lds32(pp), a1 = lds32(pp + 32), a2 = lds32(pp - 32), a3 = a0 + z0;
  const uint32_t f0 = lds32(fp), f1 = lds32(fp + 32), f2 = lds32(fp - 32), f3 = f0 + z0;
  const uint32_t e0 = lds32(fp + 64), e1 = lds32(fp + 96), e2 = f1 + z0, e3 = e0 + z0;
#pragma unroll
  for (int p = 0; p < 12; p += 2) {
    uint32_t b0, b1, b2, b3;
    ldsm4(b0, b1, b2, b3, xa + p * 1024);
    side(8 + p / 2);
    mma16816(acc[p], a0, a1, a2, a3, b0, b1);
    mma16816(acc[p + 1], a0, a1, a2, a3, b2, b3);
    if (p < 8) {
      mma16816(acc[4 + p], f0, f1, f2, f3, b0, b1);
      mma16816(acc[5 + p], f0, f1, f2, f3, b2, b3);
    }
  }
#pragma unroll
  for (int p = 0; p < 8; p += 2) {
    uint32_t b0, b1, b2, b3;
    ldsm4(b0, b1, b2, b3, xb + p * 1024);
    if (p < 4) side(14 + p / 2);
    mma16816(acc[4 + p], e0, e1, e2, e3, b0, b1);
    mma16816(acc[5 + p], e0, e1, e2, e3, b2, b3);
  }
}

template <class F> __device__ __forceinline__ void kgen(uint32_t sb, int warp, int lane, const uint32_t (&pa)[7], F midway) {
  const int mi = lane >> 3, n = lane & 7;
  const float dt = bf_round(expf(bf_lo(pa[6])));
  const uint32_t sa = sb + OFF_S + warp * KG_DUMP, sq = sb + (warp < 8 ? OFF_X + 32768 : OFF_XT + 1024 - 16384) + warp * 2048;
  TRC(dt != 123.f, 50);
  const float zl = (dt * bf_lo(pa[0])) * 1.4426950408889634f, zi = dt * bf_lo(pa[1]);
  const float hi = zi * 0.15915494f;
  const float lo = fmaf(zi, 6.4206382e-9f, fmaf(zi, 0.15915494f, -hi));
  const cf w1 = cexp_pow2(zl, hi, lo, 1.f), w128 = cexp_pow2(zl, hi, lo, 128.f);
  const cf cc = cmul(cf{bf_lo(pa[4]), bf_lo(pa[5])}, cf{dt * bf_lo(pa[2]), dt * bf_lo(pa[3])});
  TRC(w1.r + cc.r != 123.f, 48);
  float kk[5][4];
  struct Set { uint32_t r[4], i[4]; };
  auto powers = [](cf w, cf (&v)[9]) {
    v[0] = cf{1.f, 0.f}; v[1] = w;
#pragma unroll
    for (int k = 2; k < 9; k++) v[k] = (k & 1) ? cmul(v[k - 1], w) : csq(v[k / 2]);
  };
  auto pack = [](const cf (&v)[9], Set& o) {
#pragma unroll
    for (int k = 0; k < 4; k++) { o.r[k] = pack2(v[2 * k].r, v[2 * k + 1].r); o.i[k] = pack2(v[2 * k].i, v[2 * k + 1].i); }
  };
  auto scale = [](const Set& x, int x0, cf w, Set& o, int o0, int cnt) {
    const uint32_t wr = pack2(w.r, w.r), wi = pack2(w.i, w.i), wn = wi ^ 0x80008000u;
#pragma unroll
    for (int k = 0; k < cnt; k++)
      asm("{.reg .b32 s, t; mul.rn.bf16x2 s, %3, %6; mul.rn.bf16x2 t, %3, %4;\n"
          "fma.rn.bf16x2 %0, %2, %4, s; fma.rn.bf16x2 %1, %2, %5, t;}"
          : "=&r"(o.r[o0 + k]), "=r"(o.i[o0 + k]) : "r"(x.r[x0 + k]), "r"(x.i[x0 + k]), "r"(wr), "r"(wi), "r"(wn));
  };
  auto put = [&](uint32_t p, const Set& x) {
    sts128(p + lane * 16, x.r[0], x.r[1], x.r[2], x.r[3]);
    sts128(p + lane * 16 + 512, x.i[0], x.i[1], x.i[2], x.i[3]);
    __syncwarp();
  };
  uint32_t a[4][4];
  auto use = [&](int t) {
    uint32_t b[8];
    const uint32_t sp = sq + (t & 1) * 1024 + (mi & 1) * 512 + (mi >> 1) * 128 + n * 16;
    ldsm4t(b[0], b[1], b[2], b[3], sp);
    ldsm4t(b[4], b[5], b[6], b[7], sp + 256);
    __syncwarp();
    kk[t][0] = kk[t][1] = kk[t][2] = kk[t][3] = 0.f;
#pragma unroll
    for (int s = 0; s < 4; s++) mma16816(kk[t], a[s][0], a[s][1], a[s][2], a[s][3], b[2 * s], b[2 * s + 1]);
  };
#define SPLIT(i) if ((i) == MIDW) midway(); else if ((SPLM >> (i) & 1) && warp == 16 + (i)) asm volatile("trap;")
  cf u[9], t[9];
  Set su, sv, st, so;
  powers(w1, u);
  pack(u, su);
  put(sq, su);
  sv.r[0] = pack2(1.f, u[2].r); sv.i[0] = pack2(0.f, u[2].i); sv.r[1] = pack2(u[4].r, u[6].r); sv.i[1] = pack2(u[4].i, u[6].i);
  scale(su, 0, w128, so, 0, 4);
  put(sq + 1024, so);
  SPLIT(0);
  {
    const cf w8c{u[8].r, -u[8].i};
    t[0] = cf{cc.r, -cc.i};
#pragma unroll
    for (int k = 1; k < 8; k++) t[k] = cmul(t[k - 1], w8c);
    pack(t, st);
    put(sa, st);
    scale(st, 0, csq(csq(csq(w8c))), so, 0, 4);
    put(sa + 1024, so);
  }
  SPLIT(1);
#pragma unroll
  for (int s = 0; s < 4; s++) ldsm4t(a[s][0], a[s][1], a[s][2], a[s][3], sa + (mi & 1) * 1024 + (mi >> 1) * 512 + s * 128 + n * 16);
  use(0);
  powers(w128, t);
  scale(sv, 0, t[2], so, 0, 2);
  scale(sv, 0, t[3], so, 2, 2);
  put(sq, so);
  SPLIT(2);
  use(1);
  pack(t, st);
  so.r[0] = st.r[2]; so.r[1] = st.r[3]; so.i[0] = st.i[2]; so.i[1] = st.i[3];
  scale(st, 2, u[4], so, 2, 2);
  put(sq + 1024, so);
  SPLIT(3);
  use(2);
  scale(st, 0, t[8], so, 0, 4);
  put(sq, so);
  use(3);
  use(4);
  const cf w2048 = csq(t[8]);
#undef SPLIT
  TRC(true, 46);
#pragma unroll
  for (int i = 0; i < 5; i++)
    sts128(sa + i * 512 + lane * 16, __float_as_uint(kk[i][0]), __float_as_uint(kk[i][1]), __float_as_uint(kk[i][2]), __float_as_uint(kk[i][3]));
  sts32(sa + 2560 + lane * 4, __float_as_uint(fmaf(cc.r, w2048.r, -cc.i * w2048.i)));
}

__global__ void __cluster_dims__(2, 1, 1) __launch_bounds__(NTHREADS, 1) fused_kernel(const __grid_constant__ Params prm) {
  extern __shared__ __align__(1024) uint8_t smem_raw[];
  const uint32_t sb = (uint32_t)__cvta_generic_to_shared(smem_raw);
  const uint32_t bar0 = sb + OFF_BAR;
  const int warp = __shfl_sync(0xffffffffu, threadIdx.x >> 5, 0);
  int lane = threadIdx.x & 31;
  if (lane == 0) TR2(160 + warp);
  uint8_t* const scr = prm.scr;
  const int cl = ((blockIdx.x >> 1) + 60) & 63, r7 = (cl - 32) * 37 >> 8, p7 = cl - 32 - 7 * r7;
  const int mp = cl < 32 ? cl & 7 : cl < 60 ? p7 + (p7 >= GPOS) : GPOS;
  const int rnd = cl < 32 ? cl >> 3 : cl < 60 ? r7 : cl - 60;
  const int fc = FCMAP ? 2 * rnd + (cl >> 5) : rnd + 4 * (cl >> 5), rank = blockIdx.x & 1, cb = blockIdx.x;
  uint32_t pa[7];
#pragma unroll
  for (int i = 0; i < 7; i++) {
    uint16_t v;
    const int ch = cb * 4 + ((threadIdx.x >> 5) & 3);
    asm volatile("ld.global.nc" L2H ".u16 %0, [%1];" : "=h"(v) : "l"(prm.ssm[i] + (i < 6 ? ch * 128 + (threadIdx.x >> 7) * 32 + lane : ch)));
    pa[i] = v;
  }
  TRC(true, 49);
  if (warp >= 13 && elect()) asm volatile("prefetch.tensormap [%0];" ::"l"(warp == 13 ? &prm.xln : warp == 14 ? &prm.x : rank ? &prm.wu : &prm.wg) : "memory");
  if (TPF) {
    const int r = threadIdx.x >> 3, sg = threadIdx.x & 7, c0 = (min(col_a(fc), col_b(fc)) & ~31) + sg * 32;
    const __nv_bfloat16* pw = prm.w1[rank] + (mp * 64 + r) * F_ + c0;
    const __nv_bfloat16* px = prm.xp + ((2 * mp + rank) * 128 + fc * 16 + (r >> 1)) * D_ + mp * 64 + (r & 1) * 32;
    if (sg < 6 || (sg == 7 && r < 32)) asm volatile("prefetch.global.L2 [%0];" ::"l"(sg < 7 ? pw : px));
  }
  if ((sb & 0xffffff) != SB0) asm volatile("trap;");
  if ((warp >> 2) == 2 && elect()) {
#pragma unroll
    for (int i = 0; i < 10; i++) mbar_init(bar0 + 80 * (warp - 8) + 8 * i, warp > 9 ? 4 : warp == 8 || i < 8 ? 1 : i == 8 ? 2 : 16);
    if (warp == 8) mbar_init(bar0 + 8 * B_XL, 1);
    asm volatile("fence.mbarrier_init.release.cluster;" ::: "memory");
  }
  __syncwarp();
  asm volatile("barrier.cluster.arrive.relaxed.aligned;" ::: "memory");
  const int mt = 2 * mp + rank, mt2 = 2 * mp + (fc & 1), nt = (fc & 6) + rank;
  const int w = warp & 3;

  if (lane == 0) TR2(176 + warp);
  const int fa = col_a(fc), fb = col_b(fc);
  auto load_g1 = [&](int s, uint32_t xs) {
    const CUtensorMap* wm = rank ? &prm.wu : &prm.wg;
    const uint32_t fbar = bar0 + 8 * (B_F1 + s), dst = sb + OFF_W + (s & 3) * 24576 + rank * 12288;
    const int k0 = ((s + 2 * mp) & 15) * 32;
    mbar_expect(fbar, (s & 1) ? 24576 : 40960);
    if (!(s & 1)) tma2d(xs, &prm.x, fbar, k0, mt * 128);
    tma2d_mc(dst, wm, fbar, fa, k0);
    tma2d_mc(dst + 4096, wm, fbar, fa + 64, k0);
    tma2d_mc(dst + 8192, wm, fbar, fb, k0);
  };
  auto load_rows = [&]() {
          mbar_expect(bar0 + 8 * B_XL, 16384);
          asm volatile("cp.async.bulk.tensor.3d.shared::cluster.global.mbarrier::complete_tx::bytes [%0], [%1, {0, %3, 0}], [%2];"
                       ::"r"(sb + OFF_TAP), "l"(&prm.xln), "r"(bar0 + 8 * B_XL), "r"((mt * 8 + fc) * 16) : "memory");
  };
  {
    auto fill_ring = [&](int late) {
      if (warp >= 12 && (w >> 1) == late) {
        if (w == 0 && lane == 0) TR2(53);
        if (MIDW < 0 && late) __nanosleep(RING_NS);
        if (elect()) {
          if (!R2LATE || w < 2) load_g1(w, sb + OFF_X + (w >> 1) * 16384);
          if (XPF && w == 3) asm volatile("cp.async.bulk.prefetch.tensor.3d.L2.global [%0, {0, %1, 0}];" ::"l"(&prm.xln), "r"((mt * 8 + fc) * 16) : "memory");
        }
        __syncwarp();
        if (w == 0 && lane == 0) TR2(54);
      }
    };
    if (warp >= 12) {
    } else if (warp >= 8) {
      sts32(sb + OFF_STAT + lane * 4, 0x3f803f80u);
      fence_async_smem();
    } else {
      if (threadIdx.x < 48) sts128(sb + OFF_FIX + threadIdx.x * 16, 0, 0, 0, 0);
    }
    __syncwarp();
    asm volatile("barrier.cluster.wait.aligned;" ::: "memory");
    fill_ring(MIDW < 0 ? w >> 1 : 0);

    __syncwarp();
    kgen(sb, warp, lane, pa, [&]() { fill_ring(1); });
  }
  __syncwarp();
  if (lane == 0 && (!CSMODE || (warp >> 2) != 2)) mbar_arrive(bar0 + 8 * B_KG);
  if (lane == 0) TR2(224 + warp);
  int g, c, mi, n;
#define LANE_VARS() do { asm volatile("mov.u32 %0, %%laneid;" : "=r"(lane)); g = lane >> 2; c = lane & 3; mi = lane >> 3; n = lane & 7; } while (0)

  if (warp < 8) {
    asm volatile("setmaxnreg.inc.sync.aligned.u32 208;");
    LANE_VARS();
    const int wg = (warp >> 2) ^ WGSWAP;
    const bool lead = w == 0 && lane == 0;
    {
      float ag[88], au[88];
      constexpr uint32_t db0 = mkdesc(OFF_W, 4096);
      uint32_t da = mkdesc(OFF_X, 16) + wg * 512, db = db0, fbar = bar0 + 8 * B_F1, cbar;
      asm("mapa.shared::cluster.u32 %0, %1, %2;" : "=r"(cbar) : "r"(bar0 + 8 * (B_C1 - 1)), "r"(lane & 1));
      const bool sig = w == 0 && lane < 2;
      auto release = [&](int i) { if (sig) asm volatile("mbarrier.arrive.shared::cluster.b64 _, [%0];" ::"r"(cbar + 8 * i) : "memory"); };
      mbar_wait(bar0 + 8 * B_KG);
#pragma unroll 1
      for (int s = 0; s < 16; s += 2) {
#pragma unroll
        for (int k = 0; k < 2; k++) {
          mbar_wait(fbar + 8 * k);
          if (lead && (TRACE_ALL || s + k == 0)) TR(64 + wg * 16 + s + k);
          wg_fence();
          wgmma176_ss(ag, da + 4 * k, db + 1536 * k, s + k);
          wgmma176_ss(au, da + 4 * k, db + 1536 * k + 768, s + k);
          wgmma176_ss(ag, da + 4 * k + 2, db + 1536 * k + 128, 1);
          wgmma176_ss(au, da + 4 * k + 2, db + 1536 * k + 896, 1);
          wg_commit();
          wg_wait<1>();
          if (s + k > 0) release(k);
        }
        da += (s == 4 || s == 10) ? -2048 : 1024;
        db ^= 3072;
        fbar += 16; cbar += 16;
      }
      mbar_wait(bar0 + 8 * (B_F1 + 16));
      const float r0 = __uint_as_float(lds32(sb + OFF_STAT + (wg * 64 + w * 16 + g) * 4)), r1 = __uint_as_float(lds32(sb + OFF_STAT + (wg * 64 + w * 16 + g + 8) * 4));
      wg_fence();
      wgmma176_ns(ag, mkdesc(OFF_W + 2048, 0) + wg * 64, db0, 1);
      wgmma176_ns(au, mkdesc(OFF_W + 2048, 0) + wg * 64, db0 + (12288 >> 4), 1);
      wg_commit();
      wg_wait<1>();
      release(0);
      wg_wait<0>();
      release(1);
      if (lead) TR(4 + wg);
#pragma unroll
      for (int p = 0; p < 3; p++) {
        const uint32_t hs = sb + OFF_X + p * 16384 + (8 * wg + 2 * w + (mi & 1)) * (p < 2 ? 1024 : 768) + (mi >> 1) * 128 + n * 16;
#pragma unroll
        for (int j = 8 * p; j < 8 * p + 8 && j < 22; j += 2) {
          uint32_t q[4];
#pragma unroll
          for (int i = 0; i < 4; i++) {
            const int e = 4 * j + 2 * i;
            const float r = (i & 1) ? r1 : r0;
            q[i] = pack2(ag[e] * r * au[e], ag[e + 1] * r * au[e + 1]);
          }
          stsm4(hs + (j & 7) * 128, q[0], q[1], q[2], q[3]);
        }
        if (!(IFENCE & 1)) fence_async_smem();
        __syncwarp();
        if (lane == 0) mbar_arrive(bar0 + 8 * (B_ST + p));
      }
    }
    if (lead) TR(wg ? 36 : 6);
    const uint32_t to = ((mi >> 1) * 8 + n) * 128 + (((2 * w + (mi & 1)) ^ n) << 4);
    float acc[64];
    uint32_t ta[2][8][4], xq[32];
    const uint32_t pp = sb + OFF_TAP + 2 * wg * TAP_CH + (16 + 128 * (w & 2) + 8 * (w & 1) + g - 2 * c) * 4;
    auto load_taps = [&](int v) {
      const uint32_t a = pp + (v >> 3) * TAP_CH + (v & 7) * 64;
      ta[v >> 3][v & 7][0] = lds32(a); ta[v >> 3][v & 7][1] = lds32(a + 512);
      ta[v >> 3][v & 7][2] = lds32(a - 32); ta[v >> 3][v & 7][3] = lds32(a + 480);
    };
    auto near = [&](int i) {
      const uint32_t db = mkdesc(OFF_XT + 1024, 16) + (2 * wg + i) * 2;
      const int turn = 10 + 2 * i + wg;
      if (turn > 10) asm volatile("bar.sync %0, 256;" ::"r"(turn) : "memory");
      if (lead) TR2(208 + turn);
      wg_fence();
      wgmma128_rs<0>(acc, ta[i][0], db);
#pragma unroll
      for (int j0 = 1; j0 < 8; j0++) {
        if (j0 == PASSJ && turn < 13) asm volatile("bar.arrive %0, 256;" ::"r"(turn + 1) : "memory");
        wgmma128_rs<1>(acc, ta[i][j0], db - 8 * j0);
      }
      wg_commit();
      if (PASSJ == 8 && turn < 13) asm volatile("bar.arrive %0, 256;" ::"r"(turn + 1) : "memory");
      if (lead) TR2(202 + turn);
    };
    auto fold = [&](uint32_t (&q)[16]) {
      q[0] = pack2(acc[0], acc[1]);
#pragma unroll
      for (int p = 1; p < 16; p++) q[p] = pack2(acc[4 * p] + acc[4 * p - 2], acc[4 * p + 1] + acc[4 * p - 1]);
    };
    uint32_t ym[8], q[16], a[8];
    const uint32_t yo0 = (w & 2) * 1024 + mi * 256 + (w & 1) * 128 + ((n ^ (4 * (w & 1))) << 4);
    auto merge_a = [&](int i) {
      const uint32_t fr = sb + OFF_YS + wg * YS_STEP + i * 4096 + yo0, f = sb + OFF_MID + (2 * wg + i) * 4096 + yo0;
      ldsm4t(ym[0], ym[1], ym[2], ym[3], f);
      ldsm4t(ym[4], ym[5], ym[6], ym[7], f + 1024);
      ldsm4t(a[4], a[5], a[6], a[7], fr + 1024);
      if (w & 2) ldsm4t(a[0], a[1], a[2], a[3], fr);
      wg_wait<0>();
      if (i) {
        if (lead) mbar_arrive(bar0 + 8 * B_CONV);
        if (lead) TR(wg ? 32 : 31);
      }
      fold(q);
    };
    auto merge_s = [&](int i) {
      const uint32_t ex = sb + OFF_TAP + (2 * wg + i) * TAP_CH + (w & 1) * 1792;
#pragma unroll
      for (int p = 4; p < 8; p++) ym[p] = hadd2(ym[p], a[p]);
      if (w & 2) {
        sts64(ex + 1536 + lane * 8, q[0], q[1]);
        sts128(ex + 1024 + lane * 16, q[2], q[3], q[4], q[5]);
#pragma unroll
        for (int p = 0; p < 8; p++) ym[p] = hadd2(p < 4 ? hadd2(ym[p], a[p]) : ym[p], q[6 + p]);
      } else {
        sts128(ex + lane * 16, q[8], q[9], q[10], q[11]);
        sts128(ex + 512 + lane * 16, q[12], q[13], q[14], q[15]);
        ym[0] = q[0]; ym[1] = q[1]; ym[2] = q[2];
#pragma unroll
        for (int p = 3; p < 8; p++) ym[p] = hadd2(ym[p], q[p]);
      }
    };
    auto merge_b = [&](int i) {
      const uint32_t ex = sb + OFF_TAP + (2 * wg + i) * TAP_CH + (w & 1) * 1792, f = sb + OFF_YS + wg * YS_STEP + i * 4096 + yo0;
      uint4 e;
      asm volatile("bar.sync %0, 64;" ::"r"(7 + 2 * wg + (w & 1)) : "memory");
      if (w & 2) e = lds128(ex + lane * 16);
      else { const uint2 v = lds64(ex + 1536 + lane * 8); e = make_uint4(0u, 0u, v.x, v.y); }
      const uint4 v = lds128(ex + ((w & 2) ? 512 : 1024) + lane * 16);
      stsm4t(f, hadd2(ym[0], e.x), hadd2(ym[1], e.y), hadd2(ym[2], e.z), hadd2(ym[3], e.w));
      stsm4t(f + 1024, hadd2(ym[4], v.x), hadd2(ym[5], v.y), hadd2(ym[6], v.z), hadd2(ym[7], v.w));
    };
    uint32_t pbuf = sb + OFF_W + 6144 + w * 512 + lane * 16;
    uint32_t yo = sb + OFF_YS + (mi >> 1) * YS_STEP + (w * 16 + (mi & 1) * 8 + n) * 128 + ((n ^ (mi & 2) * 2) << 4);
    auto publish = [&](int i) {
      if (!(IFENCE & 2)) fence_async_smem();
      __syncwarp();
      if (lane == 0) mbar_arrive(bar0 + 8 * (B_YST + 2 * i + wg));
    };
    mbar_wait(bar0 + 8 * B_BOX);
    if (wg == 0) {
      float y[12][4];
      mbar_wait(bar0 + 8 * B_XR);
      conv_far(sb, w, lane, y, [&](int v) {
        load_taps(v);
        if (v & 1) ldsm4t(xq[2 * v - 2], xq[2 * v - 1], xq[2 * v], xq[2 * v + 1], sb + OFF_W + 3 * 8192 + to + (v >> 1) * 2048);
      });
      __syncwarp();
      if (lane == 0) { mbar_arrive(bar0 + 8 * B_HM); mbar_arrive(bar0 + 8 * B_XRD); }
      if (lead) TR(39);
      uint32_t q[24];
#pragma unroll
      for (int e = 0; e < 24; e++) { q[e] = pack2(y[e >> 1][2 * (e & 1)], y[e >> 1][2 * (e & 1) + 1]); asm volatile("" : "+r"(q[e])); }
      mbar_wait(bar0 + 8 * B_HM);
      if (lead) TR(30);
      near(0);
      const uint32_t f = sb + OFF_YS + (w >> 1) * YS_STEP + (w & 1) * 4096 + 1024 + mi * 128 + ((n ^ (4 * (mi & 1))) << 4);
#pragma unroll
      for (int p = 0; p < 6; p++) stsm4t(f + p * 512, q[4 * p], q[4 * p + 1], q[4 * p + 2], q[4 * p + 3]);
      __syncwarp();
      if (lane == 0) mbar_arrive(bar0 + 8 * B_YP);
    } else {
      float y[13][4];
      conv_mid(sb, w, lane, y, load_taps);
      __syncwarp();
      if (lane == 0) mbar_arrive(bar0 + 8 * B_HM);
      if (lead) TR(35);
      const uint32_t f = sb + OFF_MID + w * 4096 + 1024 + (mi >> 1) * 256 + (n & 1) * 128 + (4 * ((mi ^ n) & 1) + (n >> 1)) * 16;
      bar_sync<3>();
      stsm2(f - 256, pack2(y[0][0], y[0][1]), pack2(y[0][2], y[0][3]));
#pragma unroll
      for (int p = 1; p < 13; p += 2)
        stsm4(f + (p - 1) * 256, pack2(y[p][0], y[p][1]), pack2(y[p][2], y[p][3]), pack2(y[p + 1][0], y[p + 1][1]), pack2(y[p + 1][2], y[p + 1][3]));
      __syncwarp();
      if (lane == 0) mbar_arrive(bar0 + 8 * B_YP);
      near(0);
    }
    mbar_wait(bar0 + 8 * B_YP);
    merge_a(0);
    merge_s(0);
    near(1);
    merge_b(0);
    publish(0);
    asm volatile("" : "+r"(pbuf), "+r"(yo));
    merge_a(1);
    merge_s(1);
    merge_b(1);
    publish(1);
    if (lead) TR(wg ? 38 : 47);
    uint32_t(&yr)[32] = xq;
    auto load_y = [&](int u) {
      if (u == YU) { mbar_wait(bar0 + 8 * B_Y); if (lead) TR2(16); }
#pragma unroll
      for (int j = YN * (u - YU); j < YN * (u - YU + 1); j++)
        if (j >= 0 && j < 8) ldsm4(yr[4 * j], yr[4 * j + 1], yr[4 * j + 2], yr[4 * j + 3], yo ^ (j << 4));
    };
    constexpr uint32_t da0 = mkdesc(OFF_W, 4096);
#pragma unroll
    for (int u = 0; u < 8; u++) {
      mbar_wait(bar0 + 8 * (B_F2 + u));
      if (lead && (TRACE_ALL || u == 0)) TR(144 - wg * 16 + u);
      const uint32_t a = da0 + (u == 4 ? wg * 11 : (4 + 2 * u) % 12 - wg) * 512, b = mkdesc(hhome(u), 128);
      wg_fence();
      wgmma128_t<1024>(acc, a, b, u);
      wgmma128_t<1024>(acc, a + 128, b + 16, 1);
      wgmma128_t<1024>(acc, a + 256, b + 32, 1);
      if (u < 7) wgmma128_t<1024>(acc, a + 384, b + 48, 1);
      wg_commit();
      if (u >= YU && wg) load_y(u);
      if (u > 0 && u < 7 + REL6) {
        wg_wait<1>();
        if (lead) {
          mbar_arrive(bar0 + 8 * (B_C2 + u - 1));
          if (u == 6) mbar_arrive_cl(bar0 + 8 * B_PF, rank ^ 1);
        }
      }
    }
    if (wg == 0) {
      mbar_wait(bar0 + 8 * B_PF);
      uint32_t ra, rb;
      asm("mapa.shared::cluster.u32 %0, %1, %2;" : "=r"(ra) : "r"(pbuf), "r"(rank ^ 1));
      asm("mapa.shared::cluster.u32 %0, %1, %2;" : "=r"(rb) : "r"(bar0 + 8 * B_PART), "r"(rank ^ 1));
      if (!REL6) {
        wg_wait<1>();
        if (lead) mbar_arrive(bar0 + 8 * (B_C2 + 6));
      }
      wg_wait<0>();
      if (w == 0 && lane < 2) mbar_arrive(bar0 + 8 * (B_C2 + 7));
      if (lead) TR2(40);
#pragma unroll
      for (int j = 0; j < 8; j++) {
        uint32_t q[4];
#pragma unroll
        for (int i = 0; i < 4; i++) {
          const int e = 4 * j + i;
          q[i] = hadd2(pack2(acc[2 * e], acc[2 * e + 1]), xq[e]);
        }
        asm volatile("st.async.shared::cluster.mbarrier::complete_tx::bytes.v4.u32 [%0], {%1,%2,%3,%4}, [%5];"
                     ::"r"(ra + (7 + j) % 12 * 8192), "r"(q[0]), "r"(q[1]), "r"(q[2]), "r"(q[3]), "r"(rb) : "memory");
      }
      if (OP == 2 && w == 1) {
        bar_sync<2, 160>();
        if (IFENCE & 4) fence_async_smem();
        if (elect()) {
          tma2d_st(&prm.out, sb + OFF_W + 5 * 8192, nt * 64, mt2 * 128);
          bulk_commit();
          bulk_wait_read();
        }
      }
    } else {
      uint4 pr[8];
#pragma unroll
      for (int u = 8; u < 16; u++) {
        mbar_wait(bar0 + 8 * (B_F2 + u));
        if (lead) TR2(128 + u);
        wg_fence();
        const uint32_t a = da0 + ((u - 1) % 12) * 512, b = mkdesc(hhome(u), 128);
        wgmma128_t<768>(acc, a, b, 1);
        wgmma128_t<768>(acc, a + 128, b + 16, 1);
        wgmma128_t<768>(acc, a + 256, b + 32, 1);
        wg_commit();
        if (!REL6 && u == 8) {
          wg_wait<2>();
          if (lead) mbar_arrive(bar0 + 8 * (B_C2 + 6));
        }
        load_y(u);
        if (u == PU) { mbar_wait(bar0 + 8 * B_PART); if (lead) TR2(43); }
        if (u >= PU && u < 15) { pr[2 * (u - PU)] = lds128(pbuf + (7 + 2 * (u - PU)) % 12 * 8192); pr[2 * (u - PU) + 1] = lds128(pbuf + (8 + 2 * (u - PU)) % 12 * 8192); }
      }
      mbar_wait(bar0 + 8 * (B_C2 + 7));
#pragma unroll
      for (int j = 2 * (15 - PU); j < 8; j++) pr[j] = lds128(pbuf + (7 + j) % 12 * 8192);
#pragma unroll
      for (int j = 0; j < 8; j++) {
        yr[4 * j] = hadd2(yr[4 * j], pr[j].x); yr[4 * j + 1] = hadd2(yr[4 * j + 1], pr[j].y);
        yr[4 * j + 2] = hadd2(yr[4 * j + 2], pr[j].z); yr[4 * j + 3] = hadd2(yr[4 * j + 3], pr[j].w);
      }
      wg_wait<0>();
      if (lead) TR(17);
#pragma unroll
      for (int hf = 0; hf < OP; hf++) {
#pragma unroll
        for (int j = 8 / OP * hf; j < 8 / OP * (hf + 1); j++) {
          uint32_t q[4];
#pragma unroll
          for (int i = 0; i < 4; i++) {
            const int e = 4 * j + i;
            q[i] = hadd2(pack2(acc[2 * e], acc[2 * e + 1]), yr[e]);
          }
          stsm4t(sb + OFF_W + 5 * 8192 + to + j * 2048, q[0], q[1], q[2], q[3]);
        }
        if (!(IFENCE & (4 << hf))) fence_async_smem();
        if (hf < OP - 1) asm volatile("bar.arrive 2, 160;" ::: "memory");
      }
      bar_sync<1>();
      if (w == 0 && elect()) {
        if (IFENCE & 8) fence_async_smem();
        tma2d_st(&prm.out, sb + OFF_W + 5 * 8192 + (OP - 1) * 8192, nt * 64, mt2 * 128 + (OP - 1) * 64);
        bulk_commit();
        TR(18);
        bulk_wait_read();
        TR(19);
      }
    }
  } else if (warp < 12) {
    asm volatile("setmaxnreg.dec.sync.aligned.u32 72;");
    LANE_VARS();
    const int blk = mt * 8 + fc;
    const uint32_t TAP = sb + OFF_TAP + w * TAP_CH;
    const int th = w & 1, chh = w >> 1;
    uint4 xv[8];
    auto load_x = [&]() {
      mbar_wait(bar0 + 8 * B_XL);
#pragma unroll
      for (int i = 0; i < 8; i++)
        ldsm4(xv[i].x, xv[i].y, xv[i].z, xv[i].w, sb + OFF_TAP + (4 * chh + (i >> 1)) * 2048 + (8 * th + n) * 128 + (((4 * (i & 1) + mi) ^ n) << 4));
    };
    if (!CSMODE || XEARLY) load_x();
    if (!CSMODE) mbar_wait(bar0 + 8 * B_KG);
    {
      float cs[3][4];
      mbar_wait(bar0 + 8 * (B_F1 + CSS));
      mbar_wait(bar0 + 8 * (B_F1 + CSS + 1));
      if (w == 0 && lane == 0) TR2(58);
      const uint32_t da = mkdesc(OFF_W + CSS * 24576, 4096) + rank * 768;
      wg_fence();
#pragma unroll
      for (int k = 0; k < 4; k++) {
        if (CSMODE && k == KGK && lane == 0) mbar_arrive(bar0 + 8 * B_KG);
#pragma unroll
        for (int at = 0; at < 3; at++) wgmma8_t(cs[at], da + (k >> 1) * 1536 + (k & 1) * 128 + at * 256, mkdesc(OFF_STAT, 0), k);
      }
      wg_commit();
      if (CSMODE && KGK == 4 && lane == 0) mbar_arrive(bar0 + 8 * B_KG);
      wg_wait<0>();
      if (w == 0 && lane < 4) mbar_arrive_cl(bar0 + 8 * B_CS, lane & 1);
      if (CSMODE && !XEARLY) load_x();
      if (w == 0 && lane == 0) TR2(25);
#pragma unroll
      for (int at = 0; at < 3; at++) {
        const float v = (c & 2) ? cs[at][2] : cs[at][0], vh = bf_round(v);
        sts16(sb + OFF_LNO + (c & 1) * 384 + (at * 64 + w * 16 + (c & 2) * 4 + g) * 2, pack2((c & 1) ? v - vh : vh, 0.f));
      }
    }
    {
      uint32_t z = lds32(sb + OFF_STAT) & 0x40, km = z | 0xffff0000u, ks = z | 0x10000u;
      float s0 = 0.f, s1 = 0.f;
#pragma unroll
      for (int i = 0; i < 8; i++) {
        const uint32_t u[4] = {xv[i].x, xv[i].y, xv[i].z, xv[i].w};
#pragma unroll
        for (int k = 0; k < 4; k++) { s0 += __uint_as_float(u[k] * ks); s1 += __uint_as_float(u[k] & km); }
      }
      s0 += s1;
      s0 += __shfl_xor_sync(0xffffffffu, s0, 1);
      s0 += __shfl_xor_sync(0xffffffffu, s0, 2);
      const float mh = s0 * (1.f / 256.f);
      z &= __float_as_uint(mh); km = z | 0xffff0000u; ks = z | 0x10000u;
      float q0 = 0.f, q1 = 0.f;
#pragma unroll
      for (int i = 0; i < 8; i++) {
        const uint32_t u[4] = {xv[i].x, xv[i].y, xv[i].z, xv[i].w};
#pragma unroll
        for (int k = 0; k < 4; k++) {
          const float a = __uint_as_float(u[k] * ks) - mh, b = __uint_as_float(u[k] & km) - mh;
          q0 = fmaf(a, a, q0); q1 = fmaf(b, b, q1);
        }
      }
      q0 += q1;
      q0 += __shfl_xor_sync(0xffffffffu, q0, 1);
      q0 += __shfl_xor_sync(0xffffffffu, q0, 2);
      LANE_VARS();
      if (c == 0) sts64(sb + OFF_MISC + w * 64 + g * 8, __float_as_uint(mh), __float_as_uint(q0));
      bar_sync<1>();
      if (CSMODE) mbar_wait(bar0 + 8 * B_KG);
      const uint2 o = lds64(sb + OFF_MISC + (w ^ 2) * 64 + g * 8);
      const float mo = __uint_as_float(o.x), dm = mh - mo;
      const uint32_t nm = pack2(-0.5f * (mh + mo), -0.5f * (mh + mo));
      const float var = bf_round((q0 + __uint_as_float(o.y) + dm * dm * 128.f) * (1.f / 512.f));
      float sd, r;
      asm("sqrt.approx.f32 %0, %1;" : "=f"(sd) : "f"(bf_round(var + 1e-5f)));
      asm("rcp.approx.f32 %0, %1;" : "=f"(r) : "f"(bf_round(sd)));
      if (chh == 0) sts32(sb + OFF_LNO + 768 + th * 128 + lane * 4, nm);
      else if (c == 0) sts32(sb + OFF_LNO + 1024 + th * 32 + g * 4, __float_as_uint(r * r));
      const uint32_t rh = pack2(r, r), rl = pack2(r - bf_lo(rh), r - bf_lo(rh));
      const uint32_t xs = swz(sb + OFF_XT + 1024 + (64 * chh + 2 * mi + (n >> 2)) * 128 + ((cpos(n & 3, th) ^ (blk & 7)) << 4));
#pragma unroll
      for (int i = 0; i < 8; i++) {
        const uint32_t u[4] = {xv[i].x, xv[i].y, xv[i].z, xv[i].w};
        uint32_t q[4];
#pragma unroll
        for (int k = 0; k < 4; k++) {
          const uint32_t dd = hadd2(u[k], nm);
          asm("{.reg .b32 t; mul.rn.bf16x2 t, %1, %3; fma.rn.bf16x2 %0, %1, %2, t;}" : "=r"(q[k]) : "r"(dd), "r"(rh), "r"(rl));
        }
        stsm4t(xs + i * 1024, q[0], q[1], q[2], q[3]);
      }
    }
    fence_async_smem();
    __syncwarp();
    LANE_VARS();
    if (lane == 0) mbar_arrive(bar0 + 8 * B_LNST);
    if (w == 0 && lane == 0) TR(24);
    {
#pragma unroll
      for (int i = 0; i < 7; i++) sts128(TAP + i * 512 + lane * 16, 0, 0, 0, 0);
      __syncwarp();
      float kk[5][4];
      const float dsk = __bfloat162float(prm.dskip[cb * 4 + w]);
      float k2048 = 0.f;
#pragma unroll
      for (int i = 0; i < 5; i++) kk[i][0] = kk[i][1] = kk[i][2] = kk[i][3] = 0.f;
#pragma unroll 1
      for (int u = 0; u < 4; u++) {
        const uint32_t dp = sb + OFF_S + (4 * u + w) * KG_DUMP;
#pragma unroll
        for (int i = 0; i < 5; i++) {
          const uint4 v = lds128(dp + i * 512 + lane * 16);
          kk[i][0] += __uint_as_float(v.x); kk[i][1] += __uint_as_float(v.y); kk[i][2] += __uint_as_float(v.z); kk[i][3] += __uint_as_float(v.w);
        }
        k2048 += __uint_as_float(lds32(dp + 2560 + lane * 4));
      }
#pragma unroll
      for (int o = 16; o; o >>= 1) k2048 += __shfl_xor_sync(0xffffffffu, k2048, o);
      const float k512 = bf_round(__shfl_sync(0xffffffffu, kk[3][0], 0));
      if (lane == 0) kk[0][0] += dsk;
      if (lane == 31) kk[2][3] -= k512;
#pragma unroll
      for (int h = 0; h < 2; h++) {
        const int a = g + 8 * h;
#pragma unroll
        for (int i = 0; i < 2; i++) {
          const uint32_t p = pack2(kk[i][2 * h + 1], kk[i][2 * h]), ad = TAP + (16 + 128 * i + 8 * a + 2 * c) * 4;
          sts16(ad, p >> 16); sts32(ad + 4, p); sts16(ad + 10, p);
        }
        {
          const int L = 256 + 128 * (c >> 1) + 4 * (c & 1) + 8 * a;
          const uint32_t p = pack2(kk[2][2 * h + 1], kk[2][2 * h]), p0 = __byte_perm(p, p, 0x3232), ad = TAP + (16 + L) * 4;
          if (L != 256) { sts16(ad - 4, p0); sts16(ad + 2, p0); }
          sts16(ad, p0); sts32(ad + 4, p0); sts32(ad + 8, p); sts16(ad + 14, p);
        }
        {
          const uint32_t p = pack2(kk[3][2 * h], kk[3][2 * h + 1]), ad = TAP + ((c & 2) ? TAP_3 : TAP_5) + (8 + 32 * (c & 1) + a) * 4;
          sts16(ad, p); sts16(ad + 6, p);
          sts16(ad + 64, p >> 16); sts16(ad + 70, p >> 16);
        }
        {
          const uint32_t p = pack2(kk[4][2 * h], kk[4][2 * h + 1]);
          const uint32_t ad = TAP + ((a & 1) ? TAP_7 : TAP_9) + (16 + 16 * c + (a >> 1)) * 4;
          if (h == 0 && lane == 0) {
            sts16(TAP + TAP_5 + 72 * 4, p); sts16(TAP + TAP_5 + 72 * 4 + 6, p);
            const uint32_t fp = sb + OFF_FIX + w * 192 + 19 * 4;
            sts16(fp, p); sts32(fp + 4, __byte_perm(p, p, 0x1010)); sts16(fp + 10, p);
            sts16(TAP + TAP_9 + 80 * 4, pack2(k2048, 0.f));
          } else { sts16(ad, p); sts16(ad + 6, p); }
          sts16(ad + 32, p >> 16); sts16(ad + 38, p >> 16);
        }
      }
    }
    if (w == 0 && lane == 0) TR2(27);
    bar_sync<1>();
    if (lane < 16) sts128(swz(sb + OFF_XT + (lane >> 1) * 128 + cpos(w, lane & 1) * 16), 0, 0, 0, 0);
    __syncwarp();
    mbar_wait(bar0 + 8 * B_XT);
    if (w == 0 && lane == 0) TR2(28);
    {
      const uint32_t S = sb + OFF_S + w * SA_CH, SB = sb + OFF_SB + w * SB_CH, xt = sb + OFF_XT + 1024;
      if (lane < 16) sts128(lane < 7 ? S + S_5 + lane * 16 : lane == 7 ? SB + S_9 : S + S_3 + (lane - 8) * 16, 0, 0, 0, 0);
      if (lane < 8) {
        float s = 0.f;
#pragma unroll
        for (int k = 0; k < 5; k++) {
          const int t = 1526 + lane + k;
          s += bf_lo(lds16(swz(xt + (t >> 4) * 128 + cpos(w, (t >> 3) & 1) * 16) + (t & 7) * 2));
        }
        sts16(S + S_5 + 199 * 16 + lane * 2, pack2(s, 0.f));
      }
#pragma unroll 1
      for (int it = 0; it < 3; it++) {
        const int b = it * 32 + lane;
        const uint32_t a0 = swz(xt + (b - 1) * 128 + cpos(w, 0) * 16), a1 = swz(xt + b * 128 + cpos(w, 0) * 16);
        const uint2 u0 = lds64(a0 + 8);
        const uint4 u1 = lds128(a0 ^ 16), u2 = lds128(a1), u3 = lds128(a1 ^ 16);
        const uint32_t u[13] = {u0.x, u0.y, u1.x, u1.y, u1.z, u1.w, u2.x, u2.y, u2.z, u2.w, u3.x, u3.y, u3.z};
        float p[26];
        p[0] = 0.f;
#pragma unroll
        for (int i = 0; i < 25; i++) p[i + 1] = (i ? p[i] : 0.f) + ((i & 1) ? bf_hi(u[i >> 1]) : bf_lo(u[i >> 1]));
#define BOX(w, i) pack2(p[(i) + (w) + 1] - p[(i) - (w)], p[(i) + (w) + 2] - p[(i) - (w) + 1])
#define BOX8(ad, w, i) sts128(ad, BOX(w, i), BOX(w, (i) + 2), BOX(w, (i) + 4), BOX(w, (i) + 6))
        const uint32_t o7 = ((2 * b + 7) ^ ((2 * b + 7) >> 3 & 1)) << 4, o8 = ((2 * b + 8) ^ (~b >> 2 & 1)) << 4;
        BOX8(S + S_5 + o7, 2, 4);
        BOX8(S + S_5 + o8, 2, 12);
        BOX8(S + S_3 + o8, 1, 8);
        BOX8(S + S_3 + (o8 ^ 16), 1, 16);
        if (it < 2) {
          BOX8(SB + S_7 + b * 16, 3, 4);
          BOX8(SB + S_7 + 1024 + b * 16, 3, 12);
          BOX8(SB + S_9 + 1024 + b * 16, 4, 4);
          if (b < 63) BOX8(SB + S_9 + (b + 1) * 16, 4, 12);
        }
#undef BOX8
#undef BOX
      }
    }
    __syncwarp();
    if (lane == 0) mbar_arrive(bar0 + 8 * B_BOX);
    if (w == 0 && lane == 0) TR(29);
  } else {
    if (R2LATE == 1 && w >= 2 && elect()) load_g1(w, sb + OFF_X + 16384);
    if (R2LATE != 2 && w == 1 && elect()) load_rows();
    __syncwarp();
    asm volatile("setmaxnreg.dec.sync.aligned.u32 24;");
    if (R2LATE == 2 && w >= 1 && elect()) { if (w == 1) load_rows(); else load_g1(w, sb + OFF_X + 16384); }
    __syncwarp();
    mbar_wait(bar0 + 8 * B_KG);
    LANE_VARS();
    if (w == 0) {
      uint32_t xs = sb + OFF_X + 32768;
      fence_async_smem();
#pragma unroll 1
      for (int s = 4; s < 16; s++) {
        if (s == CSS + 4) mbar_wait(bar0 + 8 * B_CS);
        mbar_wait(bar0 + 8 * (B_C1 + s - 4));
        if (lane == 0) TR2(96 + s);
        if (elect()) load_g1(s, xs);
        __syncwarp();
        if (s & 1) xs = xs == sb + OFF_X + 32768 ? sb + OFF_X : xs + 16384;
        if (lane == 0) TR2(112 + s);
      }
      mbar_wait(bar0 + 8 * B_LN);
      fence_async_gmem();
      mbar_wait(bar0 + 8 * (B_C1 + 12));
      if (elect()) {
        const uint32_t fbar = bar0 + 8 * (B_F1 + 16), dst = sb + OFF_W + rank * 12288;
        mbar_expect(fbar, 12288 + 2048 + 512);
        bulk_ld(sb + OFF_W + 2048, scr + G_NEGM + mt * 2048, 2048, fbar);
        bulk_ld(sb + OFF_STAT, scr + G_R2 + mt * 512, 512, fbar);
#pragma unroll 1
        for (int a = 0; a < 3; a++) tma2d_mc(dst + a * 4096, &prm.wext, fbar, fc * 192 + a * 64, rank * 16);
      }
      __syncwarp();
      mbar_wait(bar0 + 8 * (B_C1 + 13));
      if (elect()) {
        mbar_expect(bar0 + 8 * B_XR, 16384);
        tma2d(sb + OFF_W + 3 * 8192, &prm.x, bar0 + 8 * B_XR, (nt ^ 1) * 64, mt2 * 128);
      }
      __syncwarp();
#pragma unroll 1
      for (int v = 0; v < 8; v++) {
        const int u = v < 5 ? v + 1 : v == 5 ? 0 : v;
        mbar_wait(bar0 + 8 * (u == 0 ? B_XRD : u < 6 ? B_C1 + 13 + ((2 * u + 1) * 11 >> 5) : B_C2 + u - 6));
        if (u == 0) fence_async_smem();
        if (elect()) {
          const int k0 = col_a((7 * rank) ^ (u & 3)) + (u & 4) * 16;
          mbar_expect(bar0 + 8 * (B_F2 + u), 16384);
          tma2d(sb + OFF_W + (u < 5 ? 3 + 2 * u : 2 * u - 9) * 8192, &prm.w2, bar0 + 8 * (B_F2 + u), nt * 64, k0);
          tma2d(sb + OFF_W + (u < 4 ? 4 + 2 * u : 2 * u - 8) * 8192, &prm.w2, bar0 + 8 * (B_F2 + u), (nt ^ 1) * 64, k0);
        }
        __syncwarp();
        if (u == 5 && lane == 0) TR2(41);
      }
      uint32_t ws = sb + OFF_W + 7 * 8192;
#pragma unroll 1
      for (int b = 0; b < 8; b++) {
        mbar_wait(bar0 + 8 * (B_C2 + 2 + (b >> 1)));
        if (elect()) {
          mbar_expect(bar0 + 8 * (B_F2 + 8 + b), 6144);
          tma2d(ws, &prm.w2s, bar0 + 8 * (B_F2 + 8 + b), nt * 64, col_b(b));
        }
        __syncwarp();
        ws = b == 4 ? sb + OFF_W : ws + 8192;
      }
      if (elect()) {
        mbar_expect(bar0 + 8 * B_PART, 16384);
        if (OUTPF) asm volatile("prefetch.tensormap [%0];" ::"l"(&prm.out) : "memory");
      }
    } else if (w == 1) {
      const uint32_t ep = ld_relaxed(scr + G_CNT + C_EP * 256) + 1;
      const int blk = mt * 8 + fc;
      if (lane == 0) sts32(sb + OFF_MISC + 256, ep);
      mbar_wait(bar0 + 8 * B_LNST);
#pragma unroll 1
      for (int q = 0; q < 4; q++) {
        if (elect()) tma2d_st(&prm.xt, sb + OFF_XT + 1024 + q * 4096, blk * 64, q * 32);
        __nanosleep(XT_NS);
      }
      if (elect()) {
        bulk_st(scr + G_WEXT + (rank * 16 + mp * 2) * 3072 + fc * 384, sb + OFF_LNO, 384);
        bulk_st(scr + G_WEXT + (rank * 16 + mp * 2 + 1) * 3072 + fc * 384, sb + OFF_LNO + 384, 384);
        bulk_st(scr + G_NEGM + blk * 256, sb + OFF_LNO + 768, 256);
        bulk_st(scr + G_R2 + blk * 64, sb + OFF_LNO + 1024, 64);
      }
      bulk_commit();
      bulk_wait<0>();
      __syncwarp();
      if (lane < 4) signal(scr, C_LN + lane * 8 + fc);
      if (lane == 0) TR2(26);
      poll(scr, C_LN + (mp & 3) * 8 + n, ep * 16);
      if (elect()) {
        mbar_expect(bar0 + 8 * B_XT, 16384);
        bulk_ld(sb + OFF_XT + 1024, scr + G_XT + cb * 16384, 16384, bar0 + 8 * B_XT);
      }
      if (lane == 0) {
        mbar_arrive(bar0 + 8 * B_LN);
        if (cb == 0) *reinterpret_cast<uint32_t*>(scr + G_CNT + C_EP * 256) = ep;
        TR2(34);
      }
      mbar_wait(bar0 + 8 * B_LN);
#pragma unroll
      for (int k = 0; k < 4; k++) {
        mbar_wait(bar0 + 8 * (B_YST + k));
        if (IFENCE & 2) fence_async_smem();
        if (elect()) bulk_st(scr + G_YT + cb * 16384 + (2 * (k & 1) + (k >> 1)) * 4096, sb + OFF_YS + (k & 1) * YS_STEP + (k >> 1) * 4096, 4096);
      }
      bulk_commit();
      bulk_wait<0>();
      __syncwarp();
      if (lane == 0) { signal(scr, C_Y + (cb >> 4)); TR2(33); }
      poll(scr, C_Y + nt, ep * 16);
      if (lane == 0) TR2(37);
      if (elect()) {
        mbar_expect(bar0 + 8 * B_Y, 16384);
        tma2d(sb + OFF_YS, &prm.yt, bar0 + 8 * B_Y, mt2 * 128, nt * 64);
        tma2d(sb + OFF_YS + YS_STEP, &prm.yt, bar0 + 8 * B_Y, mt2 * 128 + 64, nt * 64);
      }
    } else {
      const uint8_t* hp = scr + G_H + mt2 * 24 * 16384;
      auto load_h = [&](int u) {
        if (lane == 0) TR2(192 + u);
        if (elect()) {
          const int bytes = u < 8 ? 16384 : 12288, i = u < 8 ? (u & 4) * 2 + ((7 * rank) ^ (u & 3)) : u + 8;
          mbar_expect(bar0 + 8 * (B_F2 + u), bytes);
          bulk_ld(sb + hhome(u), hp + i * 16384, bytes, bar0 + 8 * (B_F2 + u));
        }
      };
      if (w == 3) {
#pragma unroll 1
        for (int i = B_Y; i < B_END; i++)
          if (elect()) mbar_init(bar0 + 8 * i, i < B_F2 ? 1 : i < B_XRD ? 2 : i < B_HM ? 4 : 8);
        asm volatile("fence.mbarrier_init.release.cluster;" ::: "memory");
        __syncwarp();
        if (lane == 0) mbar_arrive(bar0 + 8 * B_LN);
      } else if (cb < 88) {
        mbar_wait(bar0 + 8 * (B_C1 + 1));
        if (elect()) {
          tma2d_pf(&prm.w2, (cb & 3) * 128, (cb >> 2) * 64);
          tma2d_pf(&prm.w2, (cb & 3) * 128 + 64, (cb >> 2) * 64);
        }
      }
      mbar_wait(bar0 + 8 * B_LN);
      const uint32_t ep4 = lds32(sb + OFF_MISC + 256) * 4;
      if (w == 2) {
#pragma unroll
        for (int p = 0; p < 3; p++) {
          mbar_wait(bar0 + 8 * (B_ST + p));
          if (IFENCE & 1) fence_async_smem();
          if (elect()) bulk_st(scr + G_H + (mt * 24 + p * 8 + fc) * 16384, sb + OFF_X + p * 16384, p < 2 ? 16384 : 12288);
          bulk_commit();
          bulk_wait<0>();
          __syncwarp();
          if (lane == 0) {
            signal(scr, C_H + mt * 6 + 2 * p + (fc >> 2));
            mbar_arrive(bar0 + 8 * (B_STG + p));
            TR2(p == 0 ? 20 : p == 1 ? 21 : 7);
          }
        }
        poll(scr, C_H + mt2 * 6 + 2 + rank, ep4);
        if (lane == 0) { mbar_arrive(bar0 + 8 * B_HT); TR2(45); }
        mbar_wait(bar0 + 8 * B_CONV);
        fence_async_smem();
        load_h(4);
      } else {
        mbar_wait(bar0 + 8 * B_STG);
        poll(scr, C_H + mt2 * 6 + rank, ep4);
        load_h(0);
        mbar_wait(bar0 + 8 * (B_STG + 1));
        load_h(1);
        mbar_wait(bar0 + 8 * B_HM);
        fence_async_smem();
        load_h(2);
        mbar_wait(bar0 + 8 * (B_STG + 2));
        load_h(3);
        mbar_wait(bar0 + 8 * B_HT);
        fence_async_gmem();
      }
      mbar_wait(bar0 + 8 * (B_YST + 2));
      mbar_wait(bar0 + 8 * (B_YST + 3));
      fence_async_smem();
      load_h(8 - w);
      if (w == 3) { mbar_wait(bar0 + 8 * B_C2); load_h(7); }
      poll(scr, C_H + mt2 * 6 + 4 + (lane & 1), ep4);
#pragma unroll 1
      for (int u = 6 + w; u < 16; u += 2) {
        mbar_wait(bar0 + 8 * (B_C2 + (H_GATE >> (4 * u - 32) & 15)));
        load_h(u);
      }
    }
  }
  __syncwarp();
  TREND();
}

typedef CUresult (*EncodeFn)(CUtensorMap*, CUtensorMapDataType, cuuint32_t, void*, const cuuint64_t*, const cuuint64_t*, const cuuint32_t*,
                             const cuuint32_t*, CUtensorMapInterleave, CUtensorMapSwizzle, CUtensorMapL2promotion, CUtensorMapFloatOOBfill);

void make_map(EncodeFn enc, CUtensorMap* m, const void* p, int cols, int rows, int bc, int br, bool swz) {
  cuuint64_t gd[2] = {(cuuint64_t)cols, (cuuint64_t)rows}, gs[1] = {(cuuint64_t)cols * 2};
  cuuint32_t box[2] = {(cuuint32_t)bc, (cuuint32_t)br}, es[2] = {1, 1};
  enc(m, CU_TENSOR_MAP_DATA_TYPE_BFLOAT16, 2, const_cast<void*>(p), gd, gs, box, es, CU_TENSOR_MAP_INTERLEAVE_NONE,
      swz ? CU_TENSOR_MAP_SWIZZLE_128B : CU_TENSOR_MAP_SWIZZLE_NONE, CU_TENSOR_MAP_L2_PROMOTION_L2_128B, CU_TENSOR_MAP_FLOAT_OOB_FILL_NONE);
}

}

extern "C" void kernel_launch(void* const* d_in, const int* in_sizes, int n_in, void* d_out, int out_size) {
  EncodeFn enc = nullptr;
  cudaDriverEntryPointQueryResult qr;
  cudaGetDriverEntryPoint("cuTensorMapEncodeTiled", (void**)&enc, cudaEnableDefault, &qr);
  void* scr;
  cudaGetSymbolAddress(&scr, g_scr);
  uint8_t *xt = (uint8_t*)scr + G_XT, *yt = (uint8_t*)scr + G_YT, *wext = (uint8_t*)scr + G_WEXT;
  Params p;
  make_map(enc, &p.x, d_in[0], D_, T_, 64, 128, true);
  make_map(enc, &p.wg, d_in[10], F_, D_, 64, 32, true);
  make_map(enc, &p.wu, d_in[11], F_, D_, 64, 32, true);
  make_map(enc, &p.wext, wext, 1536, 32, 64, 16, true);
  make_map(enc, &p.w2, d_in[12], D_, F_, 64, 64, true);
  make_map(enc, &p.w2s, d_in[12], D_, F_, 64, 48, true);
  make_map(enc, &p.xt, xt, 8192, 128, 64, 32, true);
  make_map(enc, &p.yt, yt, T_, D_, 64, 64, true);
  make_map(enc, &p.out, d_out, D_, T_, 64, 128 / OP, true);
  {
    cuuint64_t gd[3] = {64, T_, 8}, gs[2] = {D_ * 2, 128};
    cuuint32_t box[3] = {64, 16, 8}, es[3] = {1, 1, 1};
    enc(&p.xln, CU_TENSOR_MAP_DATA_TYPE_BFLOAT16, 3, d_in[0], gd, gs, box, es, CU_TENSOR_MAP_INTERLEAVE_NONE, CU_TENSOR_MAP_SWIZZLE_128B,
        CU_TENSOR_MAP_L2_PROMOTION_L2_128B, CU_TENSOR_MAP_FLOAT_OOB_FILL_NONE);
  }
  p.scr = (uint8_t*)scr;
  p.xp = (const __nv_bfloat16*)d_in[0];
  p.w1[0] = (const __nv_bfloat16*)d_in[10];
  p.w1[1] = (const __nv_bfloat16*)d_in[11];
  for (int i = 0; i < 7; i++) p.ssm[i] = (const __nv_bfloat16*)d_in[1 + i];
  p.dskip = (const __nv_bfloat16*)d_in[8];
  cudaFuncSetAttribute(fused_kernel, cudaFuncAttributeMaxDynamicSharedMemorySize, SMEM_BYTES);
  fused_kernel<<<128, NTHREADS, SMEM_BYTES>>>(p);
}
```

```cpp
#include <cuda_runtime.h>
#include <cuda_bf16.h>
#include <cuda.h>
#include <stdint.h>

namespace {

constexpr int T_ = 2048, D_ = 512, F_ = 1376;
constexpr int NTHREADS = 512;

constexpr uint32_t OFF_W = 0;
constexpr uint32_t OFF_X = 98304;
constexpr uint32_t OFF_S = 147456;
constexpr uint32_t SA_CH = 6400, S_5 = 0, S_3 = 3200, OFF_SB = OFF_S + 4 * SA_CH, SB_CH = 4096, S_9 = 0, S_7 = 2048;
constexpr uint32_t KG_DUMP = 2688;
constexpr uint32_t OFF_XT = 189440;
constexpr uint32_t OFF_TAP = 206848;
constexpr uint32_t TAP_CH = 3584, TAP_5 = 2176, TAP_3 = 2528, TAP_9 = 2880, TAP_7 = 3232;
constexpr uint32_t OFF_AUX = 221184, OFF_LNO = OFF_AUX + 4096;
constexpr uint32_t OFF_YS = 180224, YS_STEP = OFF_AUX - OFF_YS;
constexpr uint32_t OFF_MID = OFF_S;
constexpr uint64_t H_HOME0 = 0x1832242e20281c18ull, H_HOME1 = 0x063225222e1f291cull;
constexpr uint32_t H_GATE = 0x66554321;
__host__ __device__ constexpr uint32_t hhome(int u) { return (uint32_t)((u < 8 ? H_HOME0 : H_HOME1) >> (8 * (u & 7)) & 255) * 4096; }
constexpr uint32_t OFF_STAT = 230144;
constexpr uint32_t OFF_MISC = 230656;
constexpr uint32_t OFF_BAR = 230976;
constexpr uint32_t SMEM_BYTES = OFF_BAR + 896 + 512;
constexpr int B_F1 = 0, B_XT = 17, B_XL = 85,
              B_LN = 18, B_KG = 19,
              B_C1 = 20, B_CS = 37, B_BOX = 38, B_LNST = 39;
constexpr int B_Y = 40, B_XR = 41, B_PART = 42, B_HT = 43, B_STG = 44,
              B_F2 = 47, B_C2 = 63, B_PF = 71, B_CONV = 72,
              B_XRD = 73, B_YST = 74,
              B_HM = 78, B_YP = 79, B_ST = 80, B_END = 83;

constexpr size_t G_XT = 0;
constexpr size_t G_YT = G_XT + 2 * D_ * T_;
constexpr size_t G_H = G_YT + 2 * D_ * T_;
constexpr size_t G_WEXT = G_H + 16 * 24 * 16384;
constexpr size_t G_NEGM = G_WEXT + 32 * 1536 * 2;
constexpr size_t G_R2 = G_NEGM + T_ * 16;
constexpr size_t G_CNT = G_R2 + T_ * 4;
constexpr int C_LN = 0, C_H = 32, C_Y = 128, C_EP = 136;
__device__ __align__(1024) uint8_t g_scr[G_CNT + 137 * 256];
constexpr bool TRACE_ALL = false;
#define TR(i) do {} while (0)
#define TR2(i) do {} while (0)
#define TRC(c, i) do {} while (0)
#define TREND() do {} while (0)

struct Params {
  const __nv_bfloat16 *ssm[7], *dskip;
  uint8_t* scr;
  CUtensorMap x, wg, wu, wext, w2, w2s, xt, yt, out, xln;
};

constexpr int SPIN_LIMIT = 1 << 13;

#define XP 4
#define XS 0
#define XN 30
__device__ __forceinline__ void mbar_init(uint32_t b, int c) { asm volatile("mbarrier.init.shared::cta.b64 [%0], %1;" ::"r"(b), "r"(c) : "memory"); }
__device__ __forceinline__ void mbar_expect(uint32_t b, int bytes) { asm volatile("mbarrier.arrive.expect_tx.shared::cta.b64 _, [%0], %1;" ::"r"(b), "r"(bytes) : "memory"); }
__device__ __forceinline__ void mbar_arrive(uint32_t b) { asm volatile("mbarrier.arrive.shared::cta.b64 _, [%0];" ::"r"(b) : "memory"); }
__device__ __forceinline__ void mbar_arrive_cl(uint32_t b, uint32_t cta) {
  asm volatile("{.reg .b32 r; mapa.shared::cluster.u32 r, %0, %1; mbarrier.arrive.shared::cluster.b64 _, [r];}" ::"r"(b), "r"(cta) : "memory");
}
__device__ __forceinline__ void mbar_wait(uint32_t b) {
  asm volatile(
      "{.reg .pred p, q; .reg .u32 n; mov.u32 n, 0;\n"
      "W: mbarrier.try_wait.parity.shared::cta.b64 p, [%0], 0;\n"
      "add.u32 n, n, 1; setp.lt.and.u32 q, n, %1, !p;\n"
      "@q bra W;}" ::"r"(b), "n"(SPIN_LIMIT) : "memory");
}
__device__ __forceinline__ void mbar_wait_cluster(uint32_t b) {
  asm volatile(
      "{.reg .pred p, q; .reg .u32 n; mov.u32 n, 0;\n"
      "W: mbarrier.try_wait.parity.acquire.cluster.shared::cta.b64 p, [%0], 0;\n"
      "add.u32 n, n, 1; setp.lt.and.u32 q, n, %1, !p;\n"
      "@q bra W;}" ::"r"(b), "n"(SPIN_LIMIT) : "memory");
}
__device__ __forceinline__ bool elect() {
  uint32_t e;
  asm volatile("{.reg .pred p; elect.sync _|p, 0xffffffff; selp.u32 %0, 1, 0, p;}" : "=r"(e));
  return e;
}
__device__ __forceinline__ void tma2d(uint32_t dst, const CUtensorMap* tm, uint32_t bar, int c0, int c1) {
  asm volatile("cp.async.bulk.tensor.2d.shared::cluster.global.mbarrier::complete_tx::bytes [%0], [%1, {%3,%4}], [%2];"
               ::"r"(dst), "l"(tm), "r"(bar), "r"(c0), "r"(c1) : "memory");
}
__device__ __forceinline__ void tma2d_mc(uint32_t dst, const CUtensorMap* tm, uint32_t bar, int c0, int c1) {
  asm volatile("cp.async.bulk.tensor.2d.shared::cluster.global.mbarrier::complete_tx::bytes.multicast::cluster [%0], [%1, {%3,%4}], [%2], %5;"
               ::"r"(dst), "l"(tm), "r"(bar), "r"(c0), "r"(c1), "h"((uint16_t)3) : "memory");
}
__device__ __forceinline__ void tma2d_st(const CUtensorMap* tm, uint32_t src, int c0, int c1) {
  asm volatile("cp.async.bulk.tensor.2d.global.shared::cta.bulk_group [%0, {%2,%3}], [%1];" ::"l"(tm), "r"(src), "r"(c0), "r"(c1) : "memory");
}
__device__ __forceinline__ void tma2d_pf(const CUtensorMap* tm, int c0, int c1) {
  asm volatile("cp.async.bulk.prefetch.tensor.2d.L2.global [%0, {%1,%2}];" ::"l"(tm), "r"(c0), "r"(c1) : "memory");
}
__device__ __forceinline__ void bulk_ld(uint32_t dst, const void* src, int bytes, uint32_t bar) {
  asm volatile("cp.async.bulk.shared::cluster.global.mbarrier::complete_tx::bytes [%0], [%1], %2, [%3];" ::"r"(dst), "l"(src), "r"(bytes), "r"(bar) : "memory");
}
__device__ __forceinline__ void bulk_st(void* dst, uint32_t src, int bytes) {
  asm volatile("cp.async.bulk.global.shared::cta.bulk_group [%0], [%1], %2;" ::"l"(dst), "r"(src), "r"(bytes) : "memory");
}
__device__ __forceinline__ void bulk_commit() { asm volatile("cp.async.bulk.commit_group;" ::: "memory"); }
__device__ __forceinline__ void bulk_wait_read() { asm volatile("cp.async.bulk.wait_group.read 0;" ::: "memory"); }
template <int N> __device__ __forceinline__ void bulk_wait() { asm volatile("cp.async.bulk.wait_group %0;" ::"n"(N) : "memory"); }
__device__ __forceinline__ void fence_async_smem() { asm volatile("fence.proxy.async.shared::cta;" ::: "memory"); }
__device__ __forceinline__ void fence_async_gmem() { asm volatile("fence.proxy.async.global;" ::: "memory"); }
template <int ID, int N = 128> __device__ __forceinline__ void bar_sync() { asm volatile("bar.sync %0, %1;" ::"n"(ID), "n"(N) : "memory"); }
__device__ __forceinline__ void signal(uint8_t* scr, int cnt) {
  asm volatile("red.relaxed.gpu.global.add.u32 [%0], 1;" ::"l"(scr + G_CNT + cnt * 256) : "memory");
}
__device__ __forceinline__ uint32_t ld_relaxed(const void* p) {
  uint32_t v;
  asm volatile("ld.relaxed.gpu.global.u32 %0, [%1];" : "=r"(v) : "l"(p) : "memory");
  return v;
}
__device__ __forceinline__ void poll(const uint8_t* scr, int cnt, uint32_t target) {
#pragma unroll 1
  for (int it = 0; it < SPIN_LIMIT * 4; it++) {
    if (__all_sync(0xffffffffu, (int)(ld_relaxed(scr + G_CNT + cnt * 256) - target) >= 0)) break;
    __nanosleep(20);
  }
  asm volatile("fence.acquire.gpu;" ::: "memory");
  fence_async_gmem();
}
__device__ __forceinline__ void wg_fence() { asm volatile("wgmma.fence.sync.aligned;" ::: "memory"); }
__device__ __forceinline__ void wg_commit() { asm volatile("wgmma.commit_group.sync.aligned;" ::: "memory"); }
template <int N> __device__ __forceinline__ void wg_wait() { asm volatile("wgmma.wait_group.sync.aligned %0;" ::"n"(N) : "memory"); }
constexpr uint32_t SB0 = 1024;
__device__ __forceinline__ constexpr uint32_t mkdesc(uint32_t off, uint32_t lbo) { return ((SB0 + off) >> 4) | ((lbo >> 4) << 16); }
__device__ __forceinline__ void wgmma176_ss(float (&d)[88], uint32_t da, uint32_t db, int acc) {
  asm volatile("{.reg .pred p; .reg .b64 a, b; setp.ne.b32 p, %90, 0; mov.b64 a, {%88, 0x40000040}; mov.b64 b, {%89, 0x40000040};\n"
    "wgmma.mma_async.sync.aligned.m64n176k16.f32.bf16.bf16 {%0,%1,%2,%3,%4,%5,%6,%7,%8,%9,%10,%11,%12,%13,%14,%15,%16,%17,%18,%19,%20,%21,%22,%23,%24,%25,%26,%27,%28,%29,%30,%31,%32,%33,%34,%35,%36,%37,%38,%39,%40,%41,%42,%43,%44,%45,%46,%47,%48,%49,%50,%51,%52,%53,%54,%55,%56,%57,%58,%59,%60,%61,%62,%63,%64,%65,%66,%67,%68,%69,%70,%71,%72,%73,%74,%75,%76,%77,%78,%79,%80,%81,%82,%83,%84,%85,%86,%87}, a, b, p, 1, 1, 0, 1;}\n"
    : "+f"(d[0]),"+f"(d[1]),"+f"(d[2]),"+f"(d[3]),"+f"(d[4]),"+f"(d[5]),"+f"(d[6]),"+f"(d[7]),"+f"(d[8]),"+f"(d[9]),"+f"(d[10]),"+f"(d[11]),"+f"(d[12]),"+f"(d[13]),"+f"(d[14]),"+f"(d[15]),"+f"(d[16]),"+f"(d[17]),"+f"(d[18]),"+f"(d[19]),"+f"(d[20]),"+f"(d[21]),"+f"(d[22]),"+f"(d[23]),"+f"(d[24]),"+f"(d[25]),"+f"(d[26]),"+f"(d[27]),"+f"(d[28]),"+f"(d[29]),"+f"(d[30]),"+f"(d[31]),"+f"(d[32]),"+f"(d[33]),"+f"(d[34]),"+f"(d[35]),"+f"(d[36]),"+f"(d[37]),"+f"(d[38]),"+f"(d[39]),"+f"(d[40]),"+f"(d[41]),"+f"(d[42]),"+f"(d[43]),"+f"(d[44]),"+f"(d[45]),"+f"(d[46]),"+f"(d[47]),"+f"(d[48]),"+f"(d[49]),"+f"(d[50]),"+f"(d[51]),"+f"(d[52]),"+f"(d[53]),"+f"(d[54]),"+f"(d[55]),"+f"(d[56]),"+f"(d[57]),"+f"(d[58]),"+f"(d[59]),"+f"(d[60]),"+f"(d[61]),"+f"(d[62]),"+f"(d[63]),"+f"(d[64]),"+f"(d[65]),"+f"(d[66]),"+f"(d[67]),"+f"(d[68]),"+f"(d[69]),"+f"(d[70]),"+f"(d[71]),"+f"(d[72]),"+f"(d[73]),"+f"(d[74]),"+f"(d[75]),"+f"(d[76]),"+f"(d[77]),"+f"(d[78]),"+f"(d[79]),"+f"(d[80]),"+f"(d[81]),"+f"(d[82]),"+f"(d[83]),"+f"(d[84]),"+f"(d[85]),"+f"(d[86]),"+f"(d[87])
    : "r"(da), "r"(db), "r"(acc));
}
__device__ __forceinline__ void wgmma176_ns(float (&d)[88], uint32_t da, uint32_t db, int acc) {
  asm volatile("{.reg .pred p; .reg .b64 a, b; setp.ne.b32 p, %90, 0; mov.b64 a, {%88, 0x00000008}; mov.b64 b, {%89, 0x40000040};\n"
    "wgmma.mma_async.sync.aligned.m64n176k16.f32.bf16.bf16 {%0,%1,%2,%3,%4,%5,%6,%7,%8,%9,%10,%11,%12,%13,%14,%15,%16,%17,%18,%19,%20,%21,%22,%23,%24,%25,%26,%27,%28,%29,%30,%31,%32,%33,%34,%35,%36,%37,%38,%39,%40,%41,%42,%43,%44,%45,%46,%47,%48,%49,%50,%51,%52,%53,%54,%55,%56,%57,%58,%59,%60,%61,%62,%63,%64,%65,%66,%67,%68,%69,%70,%71,%72,%73,%74,%75,%76,%77,%78,%79,%80,%81,%82,%83,%84,%85,%86,%87}, a, b, p, 1, 1, 0, 1;}\n"
    : "+f"(d[0]),"+f"(d[1]),"+f"(d[2]),"+f"(d[3]),"+f"(d[4]),"+f"(d[5]),"+f"(d[6]),"+f"(d[7]),"+f"(d[8]),"+f"(d[9]),"+f"(d[10]),"+f"(d[11]),"+f"(d[12]),"+f"(d[13]),"+f"(d[14]),"+f"(d[15]),"+f"(d[16]),"+f"(d[17]),"+f"(d[18]),"+f"(d[19]),"+f"(d[20]),"+f"(d[21]),"+f"(d[22]),"+f"(d[23]),"+f"(d[24]),"+f"(d[25]),"+f"(d[26]),"+f"(d[27]),"+f"(d[28]),"+f"(d[29]),"+f"(d[30]),"+f"(d[31]),"+f"(d[32]),"+f"(d[33]),"+f"(d[34]),"+f"(d[35]),"+f"(d[36]),"+f"(d[37]),"+f"(d[38]),"+f"(d[39]),"+f"(d[40]),"+f"(d[41]),"+f"(d[42]),"+f"(d[43]),"+f"(d[44]),"+f"(d[45]),"+f"(d[46]),"+f"(d[47]),"+f"(d[48]),"+f"(d[49]),"+f"(d[50]),"+f"(d[51]),"+f"(d[52]),"+f"(d[53]),"+f"(d[54]),"+f"(d[55]),"+f"(d[56]),"+f"(d[57]),"+f"(d[58]),"+f"(d[59]),"+f"(d[60]),"+f"(d[61]),"+f"(d[62]),"+f"(d[63]),"+f"(d[64]),"+f"(d[65]),"+f"(d[66]),"+f"(d[67]),"+f"(d[68]),"+f"(d[69]),"+f"(d[70]),"+f"(d[71]),"+f"(d[72]),"+f"(d[73]),"+f"(d[74]),"+f"(d[75]),"+f"(d[76]),"+f"(d[77]),"+f"(d[78]),"+f"(d[79]),"+f"(d[80]),"+f"(d[81]),"+f"(d[82]),"+f"(d[83]),"+f"(d[84]),"+f"(d[85]),"+f"(d[86]),"+f"(d[87])
    : "r"(da), "r"(db), "r"(acc));
}
template <int SBO> __device__ __forceinline__ void wgmma128_t(float (&d)[64], uint32_t da, uint32_t db, int acc) {
  asm volatile("{.reg .pred p; .reg .b64 a, b; setp.ne.b32 p, %66, 0; mov.b64 a, {%64, 0x40000040}; mov.b64 b, {%65, %67};\n"
    "wgmma.mma_async.sync.aligned.m64n128k16.f32.bf16.bf16 {%0,%1,%2,%3,%4,%5,%6,%7,%8,%9,%10,%11,%12,%13,%14,%15,%16,%17,%18,%19,%20,%21,%22,%23,%24,%25,%26,%27,%28,%29,%30,%31,%32,%33,%34,%35,%36,%37,%38,%39,%40,%41,%42,%43,%44,%45,%46,%47,%48,%49,%50,%51,%52,%53,%54,%55,%56,%57,%58,%59,%60,%61,%62,%63}, a, b, p, 1, 1, 1, 0;}\n"
    : "+f"(d[0]),"+f"(d[1]),"+f"(d[2]),"+f"(d[3]),"+f"(d[4]),"+f"(d[5]),"+f"(d[6]),"+f"(d[7]),"+f"(d[8]),"+f"(d[9]),"+f"(d[10]),"+f"(d[11]),"+f"(d[12]),"+f"(d[13]),"+f"(d[14]),"+f"(d[15]),"+f"(d[16]),"+f"(d[17]),"+f"(d[18]),"+f"(d[19]),"+f"(d[20]),"+f"(d[21]),"+f"(d[22]),"+f"(d[23]),"+f"(d[24]),"+f"(d[25]),"+f"(d[26]),"+f"(d[27]),"+f"(d[28]),"+f"(d[29]),"+f"(d[30]),"+f"(d[31]),"+f"(d[32]),"+f"(d[33]),"+f"(d[34]),"+f"(d[35]),"+f"(d[36]),"+f"(d[37]),"+f"(d[38]),"+f"(d[39]),"+f"(d[40]),"+f"(d[41]),"+f"(d[42]),"+f"(d[43]),"+f"(d[44]),"+f"(d[45]),"+f"(d[46]),"+f"(d[47]),"+f"(d[48]),"+f"(d[49]),"+f"(d[50]),"+f"(d[51]),"+f"(d[52]),"+f"(d[53]),"+f"(d[54]),"+f"(d[55]),"+f"(d[56]),"+f"(d[57]),"+f"(d[58]),"+f"(d[59]),"+f"(d[60]),"+f"(d[61]),"+f"(d[62]),"+f"(d[63])
    : "r"(da), "r"(db), "r"(acc), "n"(SBO >> 4));
}
__device__ __forceinline__ void wgmma8_t(float (&d)[4], uint32_t da, uint32_t db, int acc) {
  asm volatile("{.reg .pred p; .reg .b64 a, b; setp.ne.b32 p, %6, 0; mov.b64 a, {%4, 0x40000040}; mov.b64 b, {%5, 0x00000008};\n"
    "wgmma.mma_async.sync.aligned.m64n8k16.f32.bf16.bf16 {%0,%1,%2,%3}, a, b, p, 1, 1, 1, 0;}\n"
    : "+f"(d[0]),"+f"(d[1]),"+f"(d[2]),"+f"(d[3])
    : "r"(da), "r"(db), "r"(acc));
}
template <int ACC> __device__ __forceinline__ void wgmma128_rs(float (&d)[64], const uint32_t (&a)[4], uint32_t db) {
  asm volatile("{.reg .b64 b; mov.b64 b, {%68, 0x40000040};\n"
    "wgmma.mma_async.sync.aligned.m64n128k16.f32.bf16.bf16 {%0,%1,%2,%3,%4,%5,%6,%7,%8,%9,%10,%11,%12,%13,%14,%15,%16,%17,%18,%19,%20,%21,%22,%23,%24,%25,%26,%27,%28,%29,%30,%31,%32,%33,%34,%35,%36,%37,%38,%39,%40,%41,%42,%43,%44,%45,%46,%47,%48,%49,%50,%51,%52,%53,%54,%55,%56,%57,%58,%59,%60,%61,%62,%63}, {%64,%65,%66,%67}, b, %69, 1, 1, 0;}\n"
    : "+f"(d[0]),"+f"(d[1]),"+f"(d[2]),"+f"(d[3]),"+f"(d[4]),"+f"(d[5]),"+f"(d[6]),"+f"(d[7]),"+f"(d[8]),"+f"(d[9]),"+f"(d[10]),"+f"(d[11]),"+f"(d[12]),"+f"(d[13]),"+f"(d[14]),"+f"(d[15]),"+f"(d[16]),"+f"(d[17]),"+f"(d[18]),"+f"(d[19]),"+f"(d[20]),"+f"(d[21]),"+f"(d[22]),"+f"(d[23]),"+f"(d[24]),"+f"(d[25]),"+f"(d[26]),"+f"(d[27]),"+f"(d[28]),"+f"(d[29]),"+f"(d[30]),"+f"(d[31]),"+f"(d[32]),"+f"(d[33]),"+f"(d[34]),"+f"(d[35]),"+f"(d[36]),"+f"(d[37]),"+f"(d[38]),"+f"(d[39]),"+f"(d[40]),"+f"(d[41]),"+f"(d[42]),"+f"(d[43]),"+f"(d[44]),"+f"(d[45]),"+f"(d[46]),"+f"(d[47]),"+f"(d[48]),"+f"(d[49]),"+f"(d[50]),"+f"(d[51]),"+f"(d[52]),"+f"(d[53]),"+f"(d[54]),"+f"(d[55]),"+f"(d[56]),"+f"(d[57]),"+f"(d[58]),"+f"(d[59]),"+f"(d[60]),"+f"(d[61]),"+f"(d[62]),"+f"(d[63])
    : "r"(a[0]), "r"(a[1]), "r"(a[2]), "r"(a[3]), "r"(db), "n"(ACC));
}

__device__ __forceinline__ void mma16816(float (&d)[4], uint32_t a0, uint32_t a1, uint32_t a2, uint32_t a3, uint32_t b0, uint32_t b1) {
  asm volatile("mma.sync.aligned.m16n8k16.row.col.f32.bf16.bf16.f32 {%0,%1,%2,%3}, {%4,%5,%6,%7}, {%8,%9}, {%0,%1,%2,%3};"
               : "+f"(d[0]), "+f"(d[1]), "+f"(d[2]), "+f"(d[3]) : "r"(a0), "r"(a1), "r"(a2), "r"(a3), "r"(b0), "r"(b1));
}
__device__ __forceinline__ void ldsm4(uint32_t& r0, uint32_t& r1, uint32_t& r2, uint32_t& r3, uint32_t a) {
  asm volatile("ldmatrix.sync.aligned.m8n8.x4.shared.b16 {%0,%1,%2,%3}, [%4];" : "=r"(r0), "=r"(r1), "=r"(r2), "=r"(r3) : "r"(a) : "memory");
}
__device__ __forceinline__ void ldsm4t(uint32_t& r0, uint32_t& r1, uint32_t& r2, uint32_t& r3, uint32_t a) {
  asm volatile("ldmatrix.sync.aligned.m8n8.x4.trans.shared.b16 {%0,%1,%2,%3}, [%4];" : "=r"(r0), "=r"(r1), "=r"(r2), "=r"(r3) : "r"(a) : "memory");
}
__device__ __forceinline__ void ldsm2t(uint32_t& r0, uint32_t& r1, uint32_t a) {
  asm volatile("ldmatrix.sync.aligned.m8n8.x2.trans.shared.b16 {%0,%1}, [%2];" : "=r"(r0), "=r"(r1) : "r"(a) : "memory");
}
__device__ __forceinline__ void stsm2(uint32_t a, uint32_t r0, uint32_t r1) {
  asm volatile("stmatrix.sync.aligned.m8n8.x2.shared.b16 [%0], {%1,%2};" ::"r"(a), "r"(r0), "r"(r1) : "memory");
}
__device__ __forceinline__ void stsm4(uint32_t a, uint32_t r0, uint32_t r1, uint32_t r2, uint32_t r3) {
  asm volatile("stmatrix.sync.aligned.m8n8.x4.shared.b16 [%0], {%1,%2,%3,%4};" ::"r"(a), "r"(r0), "r"(r1), "r"(r2), "r"(r3) : "memory");
}
__device__ __forceinline__ void stsm4t(uint32_t a, uint32_t r0, uint32_t r1, uint32_t r2, uint32_t r3) {
  asm volatile("stmatrix.sync.aligned.m8n8.x4.trans.shared.b16 [%0], {%1,%2,%3,%4};" ::"r"(a), "r"(r0), "r"(r1), "r"(r2), "r"(r3) : "memory");
}
__device__ __forceinline__ uint32_t lds32(uint32_t a) { uint32_t v; asm volatile("ld.shared.u32 %0, [%1];" : "=r"(v) : "r"(a) : "memory"); return v; }
__device__ __forceinline__ uint32_t lds16(uint32_t a) { uint16_t v; asm volatile("ld.shared.u16 %0, [%1];" : "=h"(v) : "r"(a) : "memory"); return v; }
__device__ __forceinline__ uint2 lds64(uint32_t a) { uint2 v; asm volatile("ld.shared.v2.u32 {%0,%1}, [%2];" : "=r"(v.x), "=r"(v.y) : "r"(a) : "memory"); return v; }
__device__ __forceinline__ uint4 lds128(uint32_t a) { uint4 v; asm volatile("ld.shared.v4.u32 {%0,%1,%2,%3}, [%4];" : "=r"(v.x), "=r"(v.y), "=r"(v.z), "=r"(v.w) : "r"(a) : "memory"); return v; }
__device__ __forceinline__ void sts16(uint32_t a, uint32_t v) { asm volatile("st.shared.u16 [%0], %1;" ::"r"(a), "h"((uint16_t)v) : "memory"); }
__device__ __forceinline__ void sts32(uint32_t a, uint32_t v) { asm volatile("st.shared.u32 [%0], %1;" ::"r"(a), "r"(v) : "memory"); }
__device__ __forceinline__ void sts64(uint32_t a, uint32_t x, uint32_t y) { asm volatile("st.shared.v2.u32 [%0], {%1,%2};" ::"r"(a), "r"(x), "r"(y) : "memory"); }
__device__ __forceinline__ void sts128(uint32_t a, uint32_t x, uint32_t y, uint32_t z, uint32_t w) {
  asm volatile("st.shared.v4.u32 [%0], {%1,%2,%3,%4};" ::"r"(a), "r"(x), "r"(y), "r"(z), "r"(w) : "memory");
}
__device__ __forceinline__ uint32_t pack2(float lo, float hi) { uint32_t r; asm("cvt.rn.bf16x2.f32 %0, %1, %2;" : "=r"(r) : "f"(hi), "f"(lo)); return r; }
__device__ __forceinline__ uint32_t hadd2(uint32_t a, uint32_t b) { uint32_t r; asm("add.rn.bf16x2 %0, %1, %2;" : "=r"(r) : "r"(a), "r"(b)); return r; }
__device__ __forceinline__ float bf_lo(uint32_t v) { return __uint_as_float(v << 16); }
__device__ __forceinline__ float bf_hi(uint32_t v) { return __uint_as_float(v & 0xffff0000u); }
__device__ __forceinline__ float bf_round(float v) { return bf_lo(pack2(v, 0.f)); }
__device__ __forceinline__ uint32_t swz(uint32_t a) { return a ^ ((a >> 3) & 0x70); }
__device__ __forceinline__ int cpos(int ch, int half) { return 2 * ch + half; }

__device__ __forceinline__ int col_a(int f) { return __byte_perm(0x120b0700, 0x27201c17, f | 0x4440) % 256 * 32; }
__device__ __forceinline__ int col_b(int f) { return __byte_perm(0x211e0b08, 0x4b48352b, f | 0x4440) % 256 * 16; }

struct cf { float r, i; };
__device__ __forceinline__ cf cmul(cf a, cf b) { return cf{fmaf(-a.i, b.i, a.r * b.r), fmaf(a.i, b.r, a.r * b.i)}; }
__device__ __forceinline__ cf csq(cf a) { return cf{fmaf(a.r, a.r, -a.i * a.i), __fmul_rn(__fmul_rn(a.r, a.i), 2.f)}; }
__device__ __forceinline__ cf cexp_pow2(float zl, float hi, float lo, float e) {
  float h = hi * e;
  float f = fmaf(lo, e, h - rintf(h)) * 6.283185307179586f;
  float m;
  asm("ex2.approx.ftz.f32 %0, %1;" : "=f"(m) : "f"(zl * e));
  return cf{m * __cosf(f), m * __sinf(f)};
}

template <class F> __device__ __forceinline__ void conv_mid(uint32_t sb, int ch, int lane, float (&r)[13][4], F side) {
  const int g = lane >> 2, c = lane & 3;
  const uint32_t S = sb + OFF_S + ch * SA_CH, TAP = sb + OFF_TAP + ch * TAP_CH, tp = TAP + (g - 2 * c) * 4;
  const uint32_t z0 = lds32(TAP);
#pragma unroll
  for (int p = 0; p < 13; p++) r[p][0] = r[p][1] = r[p][2] = r[p][3] = 0.f;
#pragma unroll
  for (int cls = 0; cls < 2; cls++) {
    uint32_t x[13][2];
#pragma unroll
    for (int p = 0; p < 12; p += 2) ldsm4t(x[p + 1][0], x[p + 1][1], x[p + 2][0], x[p + 2][1], S + (cls ? S_3 : S_5) + 128 + p * 256 + ((lane ^ (~lane >> 3 & 1)) << 4));
    if (cls == 0) ldsm2t(x[0][0], x[0][1], S + ((lane & 8) ? S_5 : S_3) + (lane & 7) * 16);
    uint32_t a1 = z0;
#pragma unroll
    for (int m = 4; m <= 8; m++) {
      const uint32_t a2 = a1 + z0, a0 = lds32(tp + (cls ? TAP_3 : TAP_5) + (2 * m - 7) * 32), a3 = a0 + z0;
      a1 = lds32(tp + (cls ? TAP_3 : TAP_5) + (2 * m - 6) * 32);
      if (m < 8) { side(cls * 8 + 2 * (m - 4)); side(cls * 8 + 2 * (m - 4) + 1); }
#pragma unroll
      for (int pm = cls - 1; pm + m < 16; pm++) mma16816(r[m + pm - 3], a0, a1, a2, a3, x[pm + 1][0], x[pm + 1][1]);
    }
  }
}
template <class F> __device__ __forceinline__ void conv_far(uint32_t sb, int ch, int lane, float (&acc)[12][4], F side) {
  const int g = lane >> 2, c = lane & 3, mi = lane >> 3, n = lane & 7;
  const uint32_t S = sb + OFF_SB + ch * SB_CH, TAP = sb + OFF_TAP + ch * TAP_CH;
  const uint32_t z0 = lds32(TAP);
#pragma unroll
  for (int p = 0; p < 12; p++) acc[p][0] = acc[p][1] = acc[p][2] = acc[p][3] = 0.f;
#pragma unroll
  for (int cls = 0; cls < 2; cls++) {
    const uint32_t tp = TAP + TAP_9 + 4 + cls * (TAP_7 - TAP_9 - 4) + (g - 2 * c + 8) * 4;
    uint32_t u[8][2];
    u[0][1] = lds32(tp);
#pragma unroll
    for (int i = 0; i < 8; i++) { u[i][0] = lds32(tp + i * 32 + 32); if (i < 7) u[i + 1][1] = u[i][0] + z0; }
    const uint32_t sp = S + S_9 + cls * (S_7 - S_9) + (mi & 1) * 1024 + (mi >> 1) * 128 + n * 16;
#pragma unroll
    for (int s = 0; s < 4; s++) {
      uint32_t a0, a1, a2, a3;
      ldsm4t(a0, a1, a2, a3, sp + s * 256);
      side(cls * 5 + s);
      if (s == 0) side(cls * 5 + 4);
#pragma unroll
      for (int p = 2 * s; p < 8; p++) mma16816(acc[4 + p], a0, a1, a2, a3, u[p - 2 * s][0], u[p - 2 * s][1]);
    }
  }
  const uint32_t pp = TAP + (16 + 512 + g - 2 * c) * 4;
  const uint32_t xa = swz(sb + OFF_XT + 1024 + (8 * (mi >> 1) + n) * 128 + cpos(ch, mi & 1) * 16);
  const uint32_t a0 = lds32(pp), a1 = lds32(pp + 32), a2 = lds32(pp - 32), a3 = a0 + z0;
#pragma unroll
  for (int p = 0; p < 12; p += 2) {
    uint32_t b0, b1, b2, b3;
    ldsm4(b0, b1, b2, b3, xa + p * 1024);
    side(10 + p / 2);
    mma16816(acc[p], a0, a1, a2, a3, b0, b1);
    mma16816(acc[p + 1], a0, a1, a2, a3, b2, b3);
  }
}

template <class F> __device__ __forceinline__ void kgen(uint32_t sb, int warp, int lane, const uint32_t (&pa)[7], F midway) {
  const int mi = lane >> 3, n = lane & 7;
  const float dt = bf_round(expf(bf_lo(pa[6])));
  const uint32_t sa = sb + OFF_S + warp * KG_DUMP, sq = sb + (warp < 8 ? OFF_X + 32768 : OFF_XT + 1024 - 16384) + warp * 2048;
  TRC(dt != 123.f, 50);
  const float zl = (dt * bf_lo(pa[0])) * 1.4426950408889634f, zi = dt * bf_lo(pa[1]);
  const float hi = zi * 0.15915494f;
  const float lo = fmaf(zi, 6.4206382e-9f, fmaf(zi, 0.15915494f, -hi));
  const cf w1 = cexp_pow2(zl, hi, lo, 1.f), w128 = cexp_pow2(zl, hi, lo, 128.f);
  const cf cc = cmul(cf{bf_lo(pa[4]), bf_lo(pa[5])}, cf{dt * bf_lo(pa[2]), dt * bf_lo(pa[3])});
  TRC(w1.r + cc.r != 123.f, 48);
  float kk[5][4];
  struct Set { uint32_t r[4], i[4]; };
  auto powers = [](cf w, cf (&v)[9]) {
    v[0] = cf{1.f, 0.f}; v[1] = w;
#pragma unroll
    for (int k = 2; k < 9; k++) v[k] = (k & 1) ? cmul(v[k - 1], w) : csq(v[k / 2]);
  };
  auto pack = [](const cf (&v)[9], Set& o) {
#pragma unroll
    for (int k = 0; k < 4; k++) { o.r[k] = pack2(v[2 * k].r, v[2 * k + 1].r); o.i[k] = pack2(v[2 * k].i, v[2 * k + 1].i); }
  };
  auto scale = [](const Set& x, int x0, cf w, Set& o, int o0, int cnt) {
    const uint32_t wr = pack2(w.r, w.r), wi = pack2(w.i, w.i), wn = wi ^ 0x80008000u;
#pragma unroll
    for (int k = 0; k < cnt; k++)
      asm("{.reg .b32 s, t; mul.rn.bf16x2 s, %3, %6; mul.rn.bf16x2 t, %3, %4;\n"
          "fma.rn.bf16x2 %0, %2, %4, s; fma.rn.bf16x2 %1, %2, %5, t;}"
          : "=&r"(o.r[o0 + k]), "=r"(o.i[o0 + k]) : "r"(x.r[x0 + k]), "r"(x.i[x0 + k]), "r"(wr), "r"(wi), "r"(wn));
  };
  auto put = [&](uint32_t p, const Set& x) {
    sts128(p + lane * 16, x.r[0], x.r[1], x.r[2], x.r[3]);
    sts128(p + lane * 16 + 512, x.i[0], x.i[1], x.i[2], x.i[3]);
    __syncwarp();
  };
  uint32_t a[4][4];
  auto use = [&](int t) {
    uint32_t b[8];
    const uint32_t sp = sq + (t & 1) * 1024 + (mi & 1) * 512 + (mi >> 1) * 128 + n * 16;
    ldsm4t(b[0], b[1], b[2], b[3], sp);
    ldsm4t(b[4], b[5], b[6], b[7], sp + 256);
    __syncwarp();
    kk[t][0] = kk[t][1] = kk[t][2] = kk[t][3] = 0.f;
#pragma unroll
    for (int s = 0; s < 4; s++) mma16816(kk[t], a[s][0], a[s][1], a[s][2], a[s][3], b[2 * s], b[2 * s + 1]);
  };
  cf u[9], t[9];
  Set su, sv, st, so;
  powers(w1, u);
  pack(u, su);
  put(sq, su);
  sv.r[0] = pack2(1.f, u[2].r); sv.i[0] = pack2(0.f, u[2].i); sv.r[1] = pack2(u[4].r, u[6].r); sv.i[1] = pack2(u[4].i, u[6].i);
  scale(su, 0, w128, so, 0, 4);
  put(sq + 1024, so);
  {
    const cf w8c{u[8].r, -u[8].i};
    t[0] = cf{cc.r, -cc.i};
#pragma unroll
    for (int k = 1; k < 8; k++) t[k] = cmul(t[k - 1], w8c);
    pack(t, st);
    put(sa, st);
    scale(st, 0, csq(csq(csq(w8c))), so, 0, 4);
    put(sa + 1024, so);
  }
  midway();
#pragma unroll
  for (int s = 0; s < 4; s++) ldsm4t(a[s][0], a[s][1], a[s][2], a[s][3], sa + (mi & 1) * 1024 + (mi >> 1) * 512 + s * 128 + n * 16);
  use(0);
  powers(w128, t);
  scale(sv, 0, t[2], so, 0, 2);
  scale(sv, 0, t[3], so, 2, 2);
  put(sq, so);
  use(1);
  pack(t, st);
  so.r[0] = st.r[2]; so.r[1] = st.r[3]; so.i[0] = st.i[2]; so.i[1] = st.i[3];
  scale(st, 2, u[4], so, 2, 2);
  put(sq + 1024, so);
  use(2);
  scale(st, 0, t[8], so, 0, 4);
  put(sq, so);
  use(3);
  use(4);
  const cf w2048 = csq(t[8]);
  TRC(true, 46);
#pragma unroll
  for (int i = 0; i < 5; i++)
    sts128(sa + i * 512 + lane * 16, __float_as_uint(kk[i][0]), __float_as_uint(kk[i][1]), __float_as_uint(kk[i][2]), __float_as_uint(kk[i][3]));
  sts32(sa + 2560 + lane * 4, __float_as_uint(fmaf(cc.r, w2048.r, -cc.i * w2048.i)));
}

__global__ void __cluster_dims__(2, 1, 1) __launch_bounds__(NTHREADS, 1) fused_kernel(const __grid_constant__ Params prm) {
  extern __shared__ __align__(1024) uint8_t smem_raw[];
  const uint32_t sb = (uint32_t)__cvta_generic_to_shared(smem_raw);
  const uint32_t bar0 = sb + OFF_BAR;
  const int warp = __shfl_sync(0xffffffffu, threadIdx.x >> 5, 0);
  int lane = threadIdx.x & 31;
  if (lane == 0) TR2(160 + warp);
  uint8_t* const scr = prm.scr;
  const int cl = ((blockIdx.x >> 1) + 60) & 63, r7 = (cl - 32) * 37 >> 8, p7 = cl - 32 - 7 * r7;
  const int mp = cl < 32 ? cl & 7 : cl < 60 ? p7 + 1 : 0;
  const int rnd = cl < 32 ? cl >> 3 : cl < 60 ? r7 : cl - 60;
  const int fc = 2 * rnd + (cl >> 5), rank = blockIdx.x & 1, cb = blockIdx.x;
  uint32_t pa[7];
#pragma unroll
  for (int i = 0; i < 7; i++) {
    uint16_t v;
    const int ch = cb * 4 + ((threadIdx.x >> 5) & 3);
    asm volatile("ld.global.nc.L2::256B.u16 %0, [%1];" : "=h"(v) : "l"(prm.ssm[i] + (i < 6 ? ch * 128 + (threadIdx.x >> 7) * 32 + lane : ch)));
    pa[i] = v;
  }
  TRC(true, 49);
  if (warp >= 13 && elect()) asm volatile("prefetch.tensormap [%0];" ::"l"(warp == 13 ? &prm.xln : warp == 14 ? &prm.x : rank ? &prm.wu : &prm.wg) : "memory");
  if ((sb & 0xffffff) != SB0) asm volatile("trap;");
  if ((warp >> 2) == 2 && elect()) {
#pragma unroll
    for (int i = 0; i < 10; i++) mbar_init(bar0 + 80 * (warp - 8) + 8 * i, warp > 9 ? 4 : warp == 8 || i < 8 ? 1 : i == 8 ? 2 : 16);
    if (warp == 8) mbar_init(bar0 + 8 * B_XL, 1);
    asm volatile("fence.mbarrier_init.release.cluster;" ::: "memory");
  }
  __syncwarp();
  asm volatile("barrier.cluster.arrive.relaxed.aligned;" ::: "memory");
  const int mt = 2 * mp + rank, mt2 = 2 * mp + (fc & 1), nt = (fc & 6) + rank;
  const int w = warp & 3;

  if (lane == 0) TR2(176 + warp);
  const int fa = col_a(fc), fb = col_b(fc);
  auto load_g1 = [&](int s, uint32_t xs) {
    const CUtensorMap* wm = rank ? &prm.wu : &prm.wg;
    const uint32_t fbar = bar0 + 8 * (B_F1 + s), dst = sb + OFF_W + (s & 3) * 24576 + rank * 12288;
    const int k0 = ((s + 2 * mp) & 15) * 32;
    mbar_expect(fbar, (s & 1) ? 24576 : 40960);
    if (!(s & 1)) tma2d(xs, &prm.x, fbar, k0, mt * 128);
    tma2d_mc(dst, wm, fbar, fa, k0);
    tma2d_mc(dst + 4096, wm, fbar, fa + 64, k0);
    tma2d_mc(dst + 8192, wm, fbar, fb, k0);
  };
  auto load_rows = [&]() {
          mbar_expect(bar0 + 8 * B_XL, 16384);
          asm volatile("cp.async.bulk.tensor.3d.shared::cluster.global.mbarrier::complete_tx::bytes [%0], [%1, {0, %3, 0}], [%2];"
                       ::"r"(sb + OFF_TAP), "l"(&prm.xln), "r"(bar0 + 8 * B_XL), "r"((mt * 8 + fc) * 16) : "memory");
  };
  {
    auto fill_ring = [&](int late) {
      if (warp >= 12 && (w >> 1) == late) {
        if (w == 0 && lane == 0) TR2(53);
        if (elect()) {
          load_g1(w, sb + OFF_X + late * 16384);
          if (w == 3) asm volatile("cp.async.bulk.prefetch.tensor.3d.L2.global [%0, {0, %1, 0}];" ::"l"(&prm.xln), "r"((mt * 8 + fc) * 16) : "memory");
        }
        __syncwarp();
        if (w == 0 && lane == 0) TR2(54);
      }
    };
    if (warp >= 12) {
    } else if (warp >= 8) {
      sts32(sb + OFF_STAT + lane * 4, 0x3f803f80u);
      fence_async_smem();
    }
    __syncwarp();
    asm volatile("barrier.cluster.wait.aligned;" ::: "memory");
    fill_ring(0);

    __syncwarp();
    kgen(sb, warp, lane, pa, [&]() { fill_ring(1); });
  }
  __syncwarp();
  if (lane == 0 && (warp >> 2) != 2) mbar_arrive(bar0 + 8 * B_KG);
  if (lane == 0) TR2(224 + warp);
  int g, c, mi, n;
#define LANE_VARS() do { asm volatile("mov.u32 %0, %%laneid;" : "=r"(lane)); g = lane >> 2; c = lane & 3; mi = lane >> 3; n = lane & 7; } while (0)

  if (warp >= 12) {
    if (w == 1 && elect()) load_rows();
    __syncwarp();
    asm volatile("setmaxnreg.dec.sync.aligned.u32 24;");
    mbar_wait(bar0 + 8 * B_KG);
    LANE_VARS();
    if (w == 0) {
      uint32_t xs = sb + OFF_X + 32768;
      fence_async_smem();
      mbar_wait(bar0 + 8 * B_CS);
#pragma unroll 1
      for (int s = 4; s < 16; s++) {
        mbar_wait(bar0 + 8 * (B_C1 + s - 4));
        if (lane == 0) TR2(96 + s);
        if (elect()) load_g1(s, xs);
        __syncwarp();
        if (s & 1) xs = xs == sb + OFF_X + 32768 ? sb + OFF_X : xs + 16384;
        if (lane == 0) TR2(112 + s);
      }
      mbar_wait(bar0 + 8 * B_LN);
      fence_async_gmem();
      mbar_wait(bar0 + 8 * (B_C1 + 12));
      if (elect()) {
        const uint32_t fbar = bar0 + 8 * (B_F1 + 16), dst = sb + OFF_W + rank * 12288;
        mbar_expect(fbar, 12288 + 2048 + 512);
        bulk_ld(sb + OFF_W + 2048, scr + G_NEGM + mt * 2048, 2048, fbar);
        bulk_ld(sb + OFF_STAT, scr + G_R2 + mt * 512, 512, fbar);
#pragma unroll 1
        for (int a = 0; a < 3; a++) tma2d_mc(dst + a * 4096, &prm.wext, fbar, fc * 192 + a * 64, rank * 16);
      }
      __syncwarp();
      mbar_wait(bar0 + 8 * (B_C1 + 13));
      if (elect()) {
        mbar_expect(bar0 + 8 * B_XR, 16384);
        tma2d(sb + OFF_W + 3 * 8192, &prm.x, bar0 + 8 * B_XR, (nt ^ 1) * 64, mt2 * 128);
      }
      __syncwarp();
#pragma unroll 1
      for (int v = 0; v < 8; v++) {
        const int u = v < 5 ? v + 1 : v == 5 ? 0 : v;
        mbar_wait(bar0 + 8 * (u == 0 ? B_XRD : u < 6 ? B_C1 + 13 + ((2 * u + 1) * 11 >> 5) : B_C2 + u - 6));
        if (u == 0) fence_async_smem();
        if (elect()) {
          const int k0 = col_a((7 * rank) ^ (u & 3)) + (u & 4) * 16;
          mbar_expect(bar0 + 8 * (B_F2 + u), 16384);
          tma2d(sb + OFF_W + (u < 5 ? 3 + 2 * u : 2 * u - 9) * 8192, &prm.w2, bar0 + 8 * (B_F2 + u), nt * 64, k0);
          tma2d(sb + OFF_W + (u < 4 ? 4 + 2 * u : 2 * u - 8) * 8192, &prm.w2, bar0 + 8 * (B_F2 + u), (nt ^ 1) * 64, k0);
        }
        __syncwarp();
        if (u == 5 && lane == 0) TR2(41);
      }
      uint32_t ws = sb + OFF_W + 7 * 8192;
#pragma unroll 1
      for (int b = 0; b < 8; b++) {
        mbar_wait(bar0 + 8 * (B_C2 + 2 + (b >> 1)));
        if (elect()) {
          mbar_expect(bar0 + 8 * (B_F2 + 8 + b), 6144);
          tma2d(ws, &prm.w2s, bar0 + 8 * (B_F2 + 8 + b), nt * 64, col_b(b));
        }
        __syncwarp();
        ws = b == 4 ? sb + OFF_W : ws + 8192;
      }
      if (elect()) {
        mbar_expect(bar0 + 8 * B_PART, 16384);
        asm volatile("prefetch.tensormap [%0];" ::"l"(&prm.out) : "memory");
      }
    } else if (w == 1) {
      const uint32_t ep = ld_relaxed(scr + G_CNT + C_EP * 256) + 1;
      const int blk = mt * 8 + fc;
      if (lane == 0) sts32(sb + OFF_MISC + 256, ep);
      mbar_wait(bar0 + 8 * B_LNST);
#pragma unroll 1
      for (int q = 0; q < XP; q++) {
        if (XS) { mbar_wait(bar0 + 8 * (B_C1 + XS + q * 4 / XP)); __nanosleep(XN); }
        if (elect()) tma2d_st(&prm.xt, sb + OFF_XT + 1024 + q * (16384 / XP), blk * 64, q * (128 / XP));
        if (!XS) __nanosleep(XN);
      }
      if (elect()) {
        bulk_st(scr + G_WEXT + (rank * 16 + mp * 2) * 3072 + fc * 384, sb + OFF_LNO, 384);
        bulk_st(scr + G_WEXT + (rank * 16 + mp * 2 + 1) * 3072 + fc * 384, sb + OFF_LNO + 384, 384);
        bulk_st(scr + G_NEGM + blk * 256, sb + OFF_LNO + 768, 256);
        bulk_st(scr + G_R2 + blk * 64, sb + OFF_LNO + 1024, 64);
      }
      bulk_commit();
      bulk_wait<0>();
      __syncwarp();
      if (lane < 4) signal(scr, C_LN + lane * 8 + fc);
      if (lane == 0) TR2(26);
      poll(scr, C_LN + (mp & 3) * 8 + n, ep * 16);
      if (elect()) {
        mbar_expect(bar0 + 8 * B_XT, 16384);
        bulk_ld(sb + OFF_XT + 1024, scr + G_XT + cb * 16384, 16384, bar0 + 8 * B_XT);
      }
      if (lane == 0) {
        mbar_arrive(bar0 + 8 * B_LN);
        if (cb == 0) *reinterpret_cast<uint32_t*>(scr + G_CNT + C_EP * 256) = ep;
        TR2(34);
      }
      mbar_wait(bar0 + 8 * B_LN);
#pragma unroll
      for (int k = 0; k < 4; k++) {
        mbar_wait(bar0 + 8 * (B_YST + k));
        fence_async_smem();
        if (elect()) bulk_st(scr + G_YT + cb * 16384 + (2 * (k & 1) + (k >> 1)) * 4096, sb + OFF_YS + (k & 1) * YS_STEP + (k >> 1) * 4096, 4096);
      }
      bulk_commit();
      bulk_wait<0>();
      __syncwarp();
      if (lane == 0) { signal(scr, C_Y + (cb >> 4)); TR2(33); }
      poll(scr, C_Y + nt, ep * 16);
      if (lane == 0) TR2(37);
      if (elect()) {
        mbar_expect(bar0 + 8 * B_Y, 16384);
        tma2d(sb + OFF_YS, &prm.yt, bar0 + 8 * B_Y, mt2 * 128, nt * 64);
        tma2d(sb + OFF_YS + YS_STEP, &prm.yt, bar0 + 8 * B_Y, mt2 * 128 + 64, nt * 64);
      }
    } else {
      const uint8_t* hp = scr + G_H + mt2 * 24 * 16384;
      auto load_h = [&](int u) {
        if (lane == 0) TR2(192 + u);
        if (elect()) {
          const int bytes = u < 8 ? 16384 : 12288, i = u < 8 ? (u & 4) * 2 + ((7 * rank) ^ (u & 3)) : u + 8;
          mbar_expect(bar0 + 8 * (B_F2 + u), bytes);
          bulk_ld(sb + hhome(u), hp + i * 16384, bytes, bar0 + 8 * (B_F2 + u));
        }
      };
      if (w == 3) {
#pragma unroll 1
        for (int i = B_Y; i < B_END; i++)
          if (elect()) mbar_init(bar0 + 8 * i, i < B_F2 ? 1 : i < B_XRD ? 2 : i < B_HM ? 4 : 8);
        asm volatile("fence.mbarrier_init.release.cluster;" ::: "memory");
        __syncwarp();
        if (lane == 0) mbar_arrive(bar0 + 8 * B_LN);
      } else if (cb < 88) {
        mbar_wait(bar0 + 8 * (B_C1 + 1));
        if (elect()) {
          tma2d_pf(&prm.w2, (cb & 3) * 128, (cb >> 2) * 64);
          tma2d_pf(&prm.w2, (cb & 3) * 128 + 64, (cb >> 2) * 64);
        }
      }
      mbar_wait(bar0 + 8 * B_LN);
      const uint32_t ep4 = lds32(sb + OFF_MISC + 256) * 4;
      if (w == 2) {
#pragma unroll
        for (int p = 0; p < 3; p++) {
          mbar_wait(bar0 + 8 * (B_ST + p));
          fence_async_smem();
          if (elect()) bulk_st(scr + G_H + (mt * 24 + p * 8 + fc) * 16384, sb + OFF_X + p * 16384, p < 2 ? 16384 : 12288);
          bulk_commit();
          bulk_wait<0>();
          __syncwarp();
          if (lane == 0) {
            signal(scr, C_H + mt * 6 + 2 * p + (fc >> 2));
            mbar_arrive(bar0 + 8 * (B_STG + p));
            TR2(p == 0 ? 20 : p == 1 ? 21 : 7);
          }
        }
        poll(scr, C_H + mt2 * 6 + 2 + rank, ep4);
        if (lane == 0) { mbar_arrive(bar0 + 8 * B_HT); TR2(45); }
        mbar_wait(bar0 + 8 * B_CONV);
        fence_async_smem();
        load_h(4);
      } else {
        mbar_wait(bar0 + 8 * B_STG);
        poll(scr, C_H + mt2 * 6 + rank, ep4);
        load_h(0);
        mbar_wait(bar0 + 8 * (B_STG + 1));
        load_h(1);
        mbar_wait(bar0 + 8 * B_HM);
        fence_async_smem();
        load_h(2);
        mbar_wait(bar0 + 8 * (B_STG + 2));
        load_h(3);
        mbar_wait(bar0 + 8 * B_HT);
        fence_async_gmem();
      }
      mbar_wait(bar0 + 8 * (B_YST + 2));
      mbar_wait(bar0 + 8 * (B_YST + 3));
      fence_async_smem();
      load_h(8 - w);
      if (w == 3) { mbar_wait(bar0 + 8 * B_C2); load_h(7); }
      poll(scr, C_H + mt2 * 6 + 4 + (lane & 1), ep4);
#pragma unroll 1
      for (int u = 6 + w; u < 16; u += 2) {
        mbar_wait(bar0 + 8 * (B_C2 + (H_GATE >> (4 * u - 32) & 15)));
        load_h(u);
      }
    }
  } else if (warp >= 8) {
    asm volatile("setmaxnreg.dec.sync.aligned.u32 72;");
    LANE_VARS();
    const int blk = mt * 8 + fc;
    const uint32_t TAP = sb + OFF_TAP + w * TAP_CH;
    const int th = w & 1, chh = w >> 1;
    uint4 xv[8];
    auto load_x = [&]() {
      mbar_wait(bar0 + 8 * B_XL);
#pragma unroll
      for (int i = 0; i < 8; i++)
        ldsm4(xv[i].x, xv[i].y, xv[i].z, xv[i].w, sb + OFF_TAP + (4 * chh + (i >> 1)) * 2048 + (8 * th + n) * 128 + (((4 * (i & 1) + mi) ^ n) << 4));
    };
    {
      float cs[3][4];
      mbar_wait(bar0 + 8 * B_F1);
      mbar_wait(bar0 + 8 * (B_F1 + 1));
      if (w == 0 && lane == 0) TR2(58);
      const uint32_t da = mkdesc(OFF_W, 4096) + rank * 768;
      wg_fence();
#pragma unroll
      for (int k = 0; k < 4; k++) {
        if (k == 2 && lane == 0) mbar_arrive(bar0 + 8 * B_KG);
#pragma unroll
        for (int at = 0; at < 3; at++) wgmma8_t(cs[at], da + (k >> 1) * 1536 + (k & 1) * 128 + at * 256, mkdesc(OFF_STAT, 0), k);
      }
      wg_commit();
      wg_wait<0>();
      if (w == 0 && lane < 4) mbar_arrive_cl(bar0 + 8 * B_CS, lane & 1);
      load_x();
      if (w == 0 && lane == 0) TR2(25);
#pragma unroll
      for (int at = 0; at < 3; at++) {
        const float v = (c & 2) ? cs[at][2] : cs[at][0], vh = bf_round(v);
        sts16(sb + OFF_LNO + (c & 1) * 384 + (at * 64 + w * 16 + (c & 2) * 4 + g) * 2, pack2((c & 1) ? v - vh : vh, 0.f));
      }
    }
    {
      uint32_t z = lds32(sb + OFF_STAT) & 0x40, km = z | 0xffff0000u, ks = z | 0x10000u;
      float s0 = 0.f, s1 = 0.f;
#pragma unroll
      for (int i = 0; i < 8; i++) {
        const uint32_t u[4] = {xv[i].x, xv[i].y, xv[i].z, xv[i].w};
#pragma unroll
        for (int k = 0; k < 4; k++) { s0 += __uint_as_float(u[k] * ks); s1 += __uint_as_float(u[k] & km); }
      }
      s0 += s1;
      s0 += __shfl_xor_sync(0xffffffffu, s0, 1);
      s0 += __shfl_xor_sync(0xffffffffu, s0, 2);
      const float mh = s0 * (1.f / 256.f);
      z &= __float_as_uint(mh); km = z | 0xffff0000u; ks = z | 0x10000u;
      float q0 = 0.f, q1 = 0.f;
#pragma unroll
      for (int i = 0; i < 8; i++) {
        const uint32_t u[4] = {xv[i].x, xv[i].y, xv[i].z, xv[i].w};
#pragma unroll
        for (int k = 0; k < 4; k++) {
          const float a = __uint_as_float(u[k] * ks) - mh, b = __uint_as_float(u[k] & km) - mh;
          q0 = fmaf(a, a, q0); q1 = fmaf(b, b, q1);
        }
      }
      q0 += q1;
      q0 += __shfl_xor_sync(0xffffffffu, q0, 1);
      q0 += __shfl_xor_sync(0xffffffffu, q0, 2);
      LANE_VARS();
      if (c == 0) sts64(sb + OFF_MISC + w * 64 + g * 8, __float_as_uint(mh), __float_as_uint(q0));
      bar_sync<1>();
      mbar_wait(bar0 + 8 * B_KG);
      const uint2 o = lds64(sb + OFF_MISC + (w ^ 2) * 64 + g * 8);
      const float mo = __uint_as_float(o.x), dm = mh - mo;
      const uint32_t nm = pack2(-0.5f * (mh + mo), -0.5f * (mh + mo));
      const float var = bf_round((q0 + __uint_as_float(o.y) + dm * dm * 128.f) * (1.f / 512.f));
      float sd, r;
      asm("sqrt.approx.f32 %0, %1;" : "=f"(sd) : "f"(bf_round(var + 1e-5f)));
      asm("rcp.approx.f32 %0, %1;" : "=f"(r) : "f"(bf_round(sd)));
      if (chh == 0) sts32(sb + OFF_LNO + 768 + th * 128 + lane * 4, nm);
      else if (c == 0) sts32(sb + OFF_LNO + 1024 + th * 32 + g * 4, __float_as_uint(r * r));
      const uint32_t rh = pack2(r, r), rl = pack2(r - bf_lo(rh), r - bf_lo(rh));
      const uint32_t xs = swz(sb + OFF_XT + 1024 + (64 * chh + 2 * mi + (n >> 2)) * 128 + ((cpos(n & 3, th) ^ (blk & 7)) << 4));
#pragma unroll
      for (int i = 0; i < 8; i++) {
        const uint32_t u[4] = {xv[i].x, xv[i].y, xv[i].z, xv[i].w};
        uint32_t q[4];
#pragma unroll
        for (int k = 0; k < 4; k++) {
          const uint32_t dd = hadd2(u[k], nm);
          asm("{.reg .b32 t; mul.rn.bf16x2 t, %1, %3; fma.rn.bf16x2 %0, %1, %2, t;}" : "=r"(q[k]) : "r"(dd), "r"(rh), "r"(rl));
        }
        stsm4t(xs + i * 1024, q[0], q[1], q[2], q[3]);
      }
    }
    fence_async_smem();
    __syncwarp();
    LANE_VARS();
    if (lane == 0) mbar_arrive(bar0 + 8 * B_LNST);
    if (w == 0 && lane == 0) TR(24);
    {
#pragma unroll
      for (int i = 0; i < 7; i++) sts128(TAP + i * 512 + lane * 16, 0, 0, 0, 0);
      __syncwarp();
      float kk[5][4];
      const float dsk = __bfloat162float(prm.dskip[cb * 4 + w]);
      float k2048 = 0.f;
#pragma unroll
      for (int i = 0; i < 5; i++) kk[i][0] = kk[i][1] = kk[i][2] = kk[i][3] = 0.f;
#pragma unroll 1
      for (int u = 0; u < 4; u++) {
        const uint32_t dp = sb + OFF_S + (4 * u + w) * KG_DUMP;
#pragma unroll
        for (int i = 0; i < 5; i++) {
          const uint4 v = lds128(dp + i * 512 + lane * 16);
          kk[i][0] += __uint_as_float(v.x); kk[i][1] += __uint_as_float(v.y); kk[i][2] += __uint_as_float(v.z); kk[i][3] += __uint_as_float(v.w);
        }
        k2048 += __uint_as_float(lds32(dp + 2560 + lane * 4));
      }
#pragma unroll
      for (int o = 16; o; o >>= 1) k2048 += __shfl_xor_sync(0xffffffffu, k2048, o);
      const float k512 = bf_round(__shfl_sync(0xffffffffu, kk[3][0], 0));
      if (lane == 0) kk[0][0] += dsk;
      if (lane == 31) kk[2][3] -= k512;
#pragma unroll
      for (int h = 0; h < 2; h++) {
        const int a = g + 8 * h;
#pragma unroll
        for (int i = 0; i < 2; i++) {
          const uint32_t p = pack2(kk[i][2 * h + 1], kk[i][2 * h]), ad = TAP + (16 + 128 * i + 8 * a + 2 * c) * 4;
          sts16(ad, p >> 16); sts32(ad + 4, p); sts16(ad + 10, p);
        }
        {
          const int L = 256 + 128 * (c >> 1) + 4 * (c & 1) + 8 * a;
          const uint32_t p = pack2(kk[2][2 * h + 1], kk[2][2 * h]), p0 = __byte_perm(p, p, 0x3232), ad = TAP + (16 + L) * 4;
          if (L != 256) { sts16(ad - 4, p0); sts16(ad + 2, p0); }
          sts16(ad, p0); sts32(ad + 4, p0); sts32(ad + 8, p); sts16(ad + 14, p);
        }
        {
          const uint32_t p = pack2(kk[3][2 * h], kk[3][2 * h + 1]), ad = TAP + ((c & 2) ? TAP_3 : TAP_5) + (8 + 32 * (c & 1) + a) * 4;
          sts16(ad, p); sts16(ad + 6, p);
          sts16(ad + 64, p >> 16); sts16(ad + 70, p >> 16);
        }
        {
          const uint32_t p = pack2(kk[4][2 * h], kk[4][2 * h + 1]);
          const uint32_t ad = TAP + ((a & 1) ? TAP_7 : TAP_9) + (16 + 16 * c + (a >> 1)) * 4;
          if (h == 0 && lane == 0) {
            sts16(TAP + TAP_5 + 72 * 4, p); sts16(TAP + TAP_5 + 72 * 4 + 6, p);
            sts16(TAP + TAP_9 + 80 * 4, pack2(k2048, 0.f));
          } else { sts16(ad, p); sts16(ad + 6, p); }
          sts16(ad + 32, p >> 16); sts16(ad + 38, p >> 16);
        }
      }
    }
    if (w == 0 && lane == 0) TR2(27);
    bar_sync<1>();
    if (lane < 16) sts128(swz(sb + OFF_XT + (lane >> 1) * 128 + cpos(w, lane & 1) * 16), 0, 0, 0, 0);
    __syncwarp();
    mbar_wait(bar0 + 8 * B_XT);
    if (w == 0 && lane == 0) TR2(28);
    {
      const uint32_t S = sb + OFF_S + w * SA_CH, SB = sb + OFF_SB + w * SB_CH, xt = sb + OFF_XT + 1024;
      if (lane < 16) sts128(lane < 7 ? S + S_5 + lane * 16 : lane == 7 ? SB + S_9 : S + S_3 + (lane - 8) * 16, 0, 0, 0, 0);
      const float v1024 = bf_lo(lds32(TAP + TAP_5 + 72 * 4));
      if (lane < 8) {
        float s = 0.f;
#pragma unroll
        for (int k = 0; k < 5; k++) {
          const int t = 1526 + lane + k;
          s += bf_lo(lds16(swz(xt + (t >> 4) * 128 + cpos(w, (t >> 3) & 1) * 16) + (t & 7) * 2));
        }
        sts16(S + S_5 + 199 * 16 + lane * 2, pack2(s, 0.f));
      }
#pragma unroll 1
      for (int it = 0; it < 3; it++) {
        const int b = it * 32 + lane;
        const uint32_t a0 = swz(xt + (b - 1) * 128 + cpos(w, 0) * 16), a1 = swz(xt + b * 128 + cpos(w, 0) * 16);
        const uint2 u0 = lds64(a0 + 8);
        const uint4 u1 = lds128(a0 ^ 16), u2 = lds128(a1), u3 = lds128(a1 ^ 16);
        const uint32_t u[13] = {u0.x, u0.y, u1.x, u1.y, u1.z, u1.w, u2.x, u2.y, u2.z, u2.w, u3.x, u3.y, u3.z};
        float p[26];
        p[0] = 0.f;
#pragma unroll
        for (int i = 0; i < 25; i++) p[i + 1] = (i ? p[i] : 0.f) + ((i & 1) ? bf_hi(u[i >> 1]) : bf_lo(u[i >> 1]));
#define BOX(w, i) pack2(p[(i) + (w) + 1] - p[(i) - (w)], p[(i) + (w) + 2] - p[(i) - (w) + 1])
#define BOX8(ad, w, i) sts128(ad, BOX(w, i), BOX(w, (i) + 2), BOX(w, (i) + 4), BOX(w, (i) + 6))
        const uint32_t o7 = ((2 * b + 7) ^ ((2 * b + 7) >> 3 & 1)) << 4, o8 = ((2 * b + 8) ^ (~b >> 2 & 1)) << 4;
        BOX8(S + S_5 + o7, 2, 4);
        BOX8(S + S_5 + o8, 2, 12);
        BOX8(S + S_3 + o8, 1, 8);
        BOX8(S + S_3 + (o8 ^ 16), 1, 16);
        if (it < 2) {
          BOX8(SB + S_7 + b * 16, 3, 4);
          BOX8(SB + S_7 + 1024 + b * 16, 3, 12);
          BOX8(SB + S_9 + 1024 + b * 16, 4, 4);
          if (b < 63) BOX8(SB + S_9 + (b + 1) * 16, 4, 12);
#define FX(o) pack2(v1024 * (p[10 + (o)] - p[8 + (o)]), v1024 * (p[11 + (o)] - p[9 + (o)]))
          const uint32_t fx = sb + OFF_AUX + w * 2048 + (b >> 3) * 256 + (b & 7) * 16;
          sts128(fx, FX(0), FX(2), FX(4), FX(6));
          sts128(fx + 128, FX(8), FX(10), FX(12), FX(14));
#undef FX
        }
#undef BOX8
#undef BOX
      }
    }
    __syncwarp();
    if (lane == 0) mbar_arrive(bar0 + 8 * B_BOX);
    if (w == 0 && lane == 0) TR(29);
  } else {
    asm volatile("setmaxnreg.inc.sync.aligned.u32 208;");
    LANE_VARS();
    const int wg = warp >> 2;
    const bool lead = w == 0 && lane == 0;
    {
      float ag[88], au[88];
      constexpr uint32_t db0 = mkdesc(OFF_W, 4096);
      uint32_t da = mkdesc(OFF_X, 16) + wg * 512, db = db0, fbar = bar0 + 8 * B_F1, cbar;
      asm("mapa.shared::cluster.u32 %0, %1, %2;" : "=r"(cbar) : "r"(bar0 + 8 * (B_C1 - 1)), "r"(lane & 1));
      const bool sig = w == 0 && lane < 2;
      auto release = [&](int i) { if (sig) asm volatile("mbarrier.arrive.shared::cluster.b64 _, [%0];" ::"r"(cbar + 8 * i) : "memory"); };
      mbar_wait(bar0 + 8 * B_KG);
#pragma unroll 1
      for (int s = 0; s < 16; s += 2) {
#pragma unroll
        for (int k = 0; k < 2; k++) {
          mbar_wait(fbar + 8 * k);
          if (lead && (TRACE_ALL || s + k == 0)) TR(64 + wg * 16 + s + k);
          wg_fence();
          wgmma176_ss(ag, da + 4 * k, db + 1536 * k, s + k);
          wgmma176_ss(au, da + 4 * k, db + 1536 * k + 768, s + k);
          wgmma176_ss(ag, da + 4 * k + 2, db + 1536 * k + 128, 1);
          wgmma176_ss(au, da + 4 * k + 2, db + 1536 * k + 896, 1);
          wg_commit();
          wg_wait<1>();
          if (s + k > 0) release(k);
        }
        da += (s == 4 || s == 10) ? -2048 : 1024;
        db ^= 3072;
        fbar += 16; cbar += 16;
      }
      mbar_wait(bar0 + 8 * (B_F1 + 16));
      const float r0 = __uint_as_float(lds32(sb + OFF_STAT + (wg * 64 + w * 16 + g) * 4)), r1 = __uint_as_float(lds32(sb + OFF_STAT + (wg * 64 + w * 16 + g + 8) * 4));
      wg_fence();
      wgmma176_ns(ag, mkdesc(OFF_W + 2048, 0) + wg * 64, db0, 1);
      wgmma176_ns(au, mkdesc(OFF_W + 2048, 0) + wg * 64, db0 + (12288 >> 4), 1);
      wg_commit();
      wg_wait<1>();
      release(0);
      wg_wait<0>();
      release(1);
      if (lead) TR(4 + wg);
#pragma unroll
      for (int p = 0; p < 3; p++) {
        const uint32_t hs = sb + OFF_X + p * 16384 + (8 * wg + 2 * w + (mi & 1)) * (p < 2 ? 1024 : 768) + (mi >> 1) * 128 + n * 16;
#pragma unroll
        for (int j = 8 * p; j < 8 * p + 8 && j < 22; j += 2) {
          uint32_t q[4];
#pragma unroll
          for (int i = 0; i < 4; i++) {
            const int e = 4 * j + 2 * i;
            const float r = (i & 1) ? r1 : r0;
            q[i] = pack2(ag[e] * r * au[e], ag[e + 1] * r * au[e + 1]);
          }
          stsm4(hs + (j & 7) * 128, q[0], q[1], q[2], q[3]);
        }
        __syncwarp();
        if (lane == 0) mbar_arrive(bar0 + 8 * (B_ST + p));
      }
    }
    if (lead) TR(wg ? 36 : 6);
    const uint32_t to = ((mi >> 1) * 8 + n) * 128 + (((2 * w + (mi & 1)) ^ n) << 4);
    float acc[64];
    uint32_t ta[2][8][4], xq[32];
    const uint32_t pp = sb + OFF_TAP + 2 * wg * TAP_CH + (16 + 128 * (w & 2) + 8 * (w & 1) + g - 2 * c) * 4;
    auto load_taps = [&](int v) {
      const uint32_t a = pp + (v >> 3) * TAP_CH + (v & 7) * 64;
      ta[v >> 3][v & 7][0] = lds32(a); ta[v >> 3][v & 7][1] = lds32(a + 512);
      ta[v >> 3][v & 7][2] = lds32(a - 32); ta[v >> 3][v & 7][3] = lds32(a + 480);
    };
    auto near = [&](int i) {
      const uint32_t db = mkdesc(OFF_XT + 1024, 16) + (2 * wg + i) * 2;
      const int turn = 10 + 2 * i + wg;
      if (turn > 10) asm volatile("bar.sync %0, 256;" ::"r"(turn) : "memory");
      if (lead) TR2(208 + turn);
      wg_fence();
      wgmma128_rs<0>(acc, ta[i][0], db);
#pragma unroll
      for (int j0 = 1; j0 < 8; j0++) wgmma128_rs<1>(acc, ta[i][j0], db - 8 * j0);
      wg_commit();
      if (turn < 13) asm volatile("bar.arrive %0, 256;" ::"r"(turn + 1) : "memory");
      if (lead) TR2(202 + turn);
    };
    auto fold = [&](uint32_t (&q)[16]) {
      q[0] = pack2(acc[0], acc[1]);
#pragma unroll
      for (int p = 1; p < 16; p++) q[p] = pack2(acc[4 * p] + acc[4 * p - 2], acc[4 * p + 1] + acc[4 * p - 1]);
    };
    uint32_t ym[8], q[16], a[8];
    const uint32_t yo0 = (w & 2) * 1024 + mi * 256 + (w & 1) * 128 + ((n ^ (4 * (w & 1))) << 4);
    auto merge_a = [&](int i) {
      const uint32_t fr = sb + OFF_YS + wg * YS_STEP + i * 4096 + yo0, f = sb + OFF_MID + (2 * wg + i) * 4096 + yo0;
      ldsm4t(ym[0], ym[1], ym[2], ym[3], f);
      ldsm4t(ym[4], ym[5], ym[6], ym[7], f + 1024);
      ldsm4t(a[4], a[5], a[6], a[7], fr + 1024);
      if (w & 2) ldsm4t(a[0], a[1], a[2], a[3], fr);
      wg_wait<0>();
      if (i) {
        if (lead) mbar_arrive(bar0 + 8 * B_CONV);
        if (lead) TR(wg ? 32 : 31);
      }
      fold(q);
    };
    auto merge_s = [&](int i) {
      const uint32_t ex = sb + OFF_TAP + (2 * wg + i) * TAP_CH + (w & 1) * 1792;
#pragma unroll
      for (int p = 4; p < 8; p++) ym[p] = hadd2(ym[p], a[p]);
      if (w & 2) {
        sts64(ex + 1536 + lane * 8, q[0], q[1]);
        sts128(ex + 1024 + lane * 16, q[2], q[3], q[4], q[5]);
#pragma unroll
        for (int p = 0; p < 8; p++) ym[p] = hadd2(p < 4 ? hadd2(ym[p], a[p]) : ym[p], q[6 + p]);
      } else {
        sts128(ex + lane * 16, q[8], q[9], q[10], q[11]);
        sts128(ex + 512 + lane * 16, q[12], q[13], q[14], q[15]);
        ym[0] = q[0]; ym[1] = q[1]; ym[2] = q[2];
#pragma unroll
        for (int p = 3; p < 8; p++) ym[p] = hadd2(ym[p], q[p]);
      }
    };
    auto merge_b = [&](int i) {
      const uint32_t ex = sb + OFF_TAP + (2 * wg + i) * TAP_CH + (w & 1) * 1792, f = sb + OFF_YS + wg * YS_STEP + i * 4096 + yo0;
      uint4 e;
      asm volatile("bar.sync %0, 64;" ::"r"(7 + 2 * wg + (w & 1)) : "memory");
      if (w & 2) e = lds128(ex + lane * 16);
      else { const uint2 v = lds64(ex + 1536 + lane * 8); e = make_uint4(0u, 0u, v.x, v.y); }
      const uint4 v = lds128(ex + ((w & 2) ? 512 : 1024) + lane * 16);
      stsm4t(f, hadd2(ym[0], e.x), hadd2(ym[1], e.y), hadd2(ym[2], e.z), hadd2(ym[3], e.w));
      stsm4t(f + 1024, hadd2(ym[4], v.x), hadd2(ym[5], v.y), hadd2(ym[6], v.z), hadd2(ym[7], v.w));
    };
    uint32_t pbuf = sb + OFF_W + 6144 + w * 512 + lane * 16;
    uint32_t yo = sb + OFF_YS + (mi >> 1) * YS_STEP + (w * 16 + (mi & 1) * 8 + n) * 128 + ((n ^ (mi & 2) * 2) << 4);
    auto publish = [&](int i) {
      __syncwarp();
      if (lane == 0) mbar_arrive(bar0 + 8 * (B_YST + 2 * i + wg));
    };
    mbar_wait(bar0 + 8 * B_BOX);
    if (wg == 0) {
      float y[12][4];
      mbar_wait(bar0 + 8 * B_XR);
      conv_far(sb, w, lane, y, [&](int v) {
        load_taps(v);
        if (v & 1) ldsm4t(xq[2 * v - 2], xq[2 * v - 1], xq[2 * v], xq[2 * v + 1], sb + OFF_W + 3 * 8192 + to + (v >> 1) * 2048);
      });
      uint32_t fx[16];
#pragma unroll
      for (int p = 0; p < 4; p++) ldsm4t(fx[4 * p], fx[4 * p + 1], fx[4 * p + 2], fx[4 * p + 3], sb + OFF_AUX + w * 2048 + p * 512 + lane * 16);
      __syncwarp();
      if (lane == 0) { mbar_arrive(bar0 + 8 * B_HM); mbar_arrive(bar0 + 8 * B_XRD); }
      if (lead) TR(39);
      uint32_t q[24];
#pragma unroll
      for (int e = 0; e < 24; e++) {
        const float y0 = y[e >> 1][2 * (e & 1)], y1 = y[e >> 1][2 * (e & 1) + 1];
        q[e] = e < 8 ? pack2(y0, y1) : pack2(y0 + bf_lo(fx[e - 8]), y1 + bf_hi(fx[e - 8]));
      }
      bar_sync<4>();
      const uint32_t f = sb + OFF_YS + (w >> 1) * YS_STEP + (w & 1) * 4096 + 1024 + mi * 128 + ((n ^ (4 * (mi & 1))) << 4);
#pragma unroll
      for (int p = 0; p < 6; p++) stsm4t(f + p * 512, q[4 * p], q[4 * p + 1], q[4 * p + 2], q[4 * p + 3]);
      __syncwarp();
      if (lane == 0) mbar_arrive(bar0 + 8 * B_YP);
      mbar_wait(bar0 + 8 * B_HM);
      if (lead) TR(30);
      near(0);
    } else {
      float y[13][4];
      conv_mid(sb, w, lane, y, load_taps);
      __syncwarp();
      if (lane == 0) mbar_arrive(bar0 + 8 * B_HM);
      if (lead) TR(35);
      const uint32_t f = sb + OFF_MID + w * 4096 + 1024 + (mi >> 1) * 256 + (n & 1) * 128 + (4 * ((mi ^ n) & 1) + (n >> 1)) * 16;
      bar_sync<3>();
      stsm2(f - 256, pack2(y[0][0], y[0][1]), pack2(y[0][2], y[0][3]));
#pragma unroll
      for (int p = 1; p < 13; p += 2)
        stsm4(f + (p - 1) * 256, pack2(y[p][0], y[p][1]), pack2(y[p][2], y[p][3]), pack2(y[p + 1][0], y[p + 1][1]), pack2(y[p + 1][2], y[p + 1][3]));
      __syncwarp();
      if (lane == 0) mbar_arrive(bar0 + 8 * B_YP);
      near(0);
    }
    mbar_wait(bar0 + 8 * B_YP);
    merge_a(0);
    merge_s(0);
    near(1);
    merge_b(0);
    publish(0);
    asm volatile("" : "+r"(pbuf), "+r"(yo));
    merge_a(1);
    merge_s(1);
    merge_b(1);
    publish(1);
    if (lead) TR(wg ? 38 : 47);
    constexpr uint32_t da0 = mkdesc(OFF_W, 4096);
#pragma unroll
    for (int u = 0; u < 8; u++) {
      mbar_wait(bar0 + 8 * (B_F2 + u));
      if (lead && (TRACE_ALL || u == 0)) TR(144 - wg * 16 + u);
      const uint32_t a = da0 + (u == 4 ? wg * 11 : (4 + 2 * u) % 12 - wg) * 512, b = mkdesc(hhome(u), 128);
      wg_fence();
      wgmma128_t<1024>(acc, a, b, u);
      wgmma128_t<1024>(acc, a + 128, b + 16, 1);
      wgmma128_t<1024>(acc, a + 256, b + 32, 1);
      if (u < 7) wgmma128_t<1024>(acc, a + 384, b + 48, 1);
      wg_commit();
      if (u > 0 && u < 7) {
        wg_wait<1>();
        if (lead) {
          mbar_arrive(bar0 + 8 * (B_C2 + u - 1));
          if (u == 6) mbar_arrive_cl(bar0 + 8 * B_PF, rank ^ 1);
        }
      }
    }
    if (wg == 0) {
      mbar_wait(bar0 + 8 * B_PF);
      uint32_t ra, rb;
      asm("mapa.shared::cluster.u32 %0, %1, %2;" : "=r"(ra) : "r"(pbuf), "r"(rank ^ 1));
      asm("mapa.shared::cluster.u32 %0, %1, %2;" : "=r"(rb) : "r"(bar0 + 8 * B_PART), "r"(rank ^ 1));
      wg_wait<1>();
      if (lead) mbar_arrive(bar0 + 8 * (B_C2 + 6));
      wg_wait<0>();
      if (w == 0 && lane < 2) mbar_arrive(bar0 + 8 * (B_C2 + 7));
      if (lead) TR2(40);
#pragma unroll
      for (int j = 0; j < 8; j++) {
        uint32_t q[4];
#pragma unroll
        for (int i = 0; i < 4; i++) {
          const int e = 4 * j + i;
          q[i] = hadd2(pack2(acc[2 * e], acc[2 * e + 1]), xq[e]);
        }
        asm volatile("st.async.shared::cluster.mbarrier::complete_tx::bytes.v4.u32 [%0], {%1,%2,%3,%4}, [%5];"
                     ::"r"(ra + (7 + j) % 12 * 8192), "r"(q[0]), "r"(q[1]), "r"(q[2]), "r"(q[3]), "r"(rb) : "memory");
      }
      {
        const uint32_t src = sb + OFF_W + 5 * 8192 + w * 4096;
        const int row = mt2 * 128 + w * 32;
        asm volatile("bar.sync %0, 160;" ::"r"(w + 1) : "memory");
        if (elect()) tma2d_st(&prm.out, src, nt * 64, row);
        bulk_commit();
        if (w == 3 && lane == 0) TR(18);
        bulk_wait_read();
        if (w == 3 && lane == 0) TR(19);
      }
    } else {
      uint32_t yr[32];
      uint4 pr[8];
#pragma unroll
      for (int u = 8; u < 16; u++) {
        mbar_wait(bar0 + 8 * (B_F2 + u));
        if (lead) TR2(128 + u);
        wg_fence();
        const uint32_t a = da0 + ((u - 1) % 12) * 512, b = mkdesc(hhome(u), 128);
        wgmma128_t<768>(acc, a, b, 1);
        wgmma128_t<768>(acc, a + 128, b + 16, 1);
        wgmma128_t<768>(acc, a + 256, b + 32, 1);
        wg_commit();
        if (u == 8) {
          wg_wait<2>();
          if (lead) mbar_arrive(bar0 + 8 * (B_C2 + 6));
        }
        if (u == 10) { mbar_wait(bar0 + 8 * B_Y); if (lead) TR2(16); }
        if (u >= 10 && u < 14) {
#pragma unroll
          for (int j = 2 * u - 20; j < 2 * u - 18; j++) ldsm4(yr[4 * j], yr[4 * j + 1], yr[4 * j + 2], yr[4 * j + 3], yo ^ (j << 4));
        }
        if (u == 14) {
          mbar_wait_cluster(bar0 + 8 * B_PART);
          if (lead) TR2(43);
          pr[0] = lds128(pbuf + 7 * 8192);
          pr[1] = lds128(pbuf + 8 * 8192);
        }
      }
      mbar_wait(bar0 + 8 * (B_C2 + 7));
#pragma unroll
      for (int j = 2; j < 8; j++) pr[j] = lds128(pbuf + (7 + j) % 12 * 8192);
#pragma unroll
      for (int j = 0; j < 8; j++) {
        yr[4 * j] = hadd2(yr[4 * j], pr[j].x); yr[4 * j + 1] = hadd2(yr[4 * j + 1], pr[j].y);
        yr[4 * j + 2] = hadd2(yr[4 * j + 2], pr[j].z); yr[4 * j + 3] = hadd2(yr[4 * j + 3], pr[j].w);
      }
      wg_wait<0>();
      if (lead) TR(17);
#pragma unroll
      for (int hf = 0; hf < 4; hf++) {
#pragma unroll
        for (int j = 2 * hf; j < 2 * hf + 2; j++) {
          uint32_t q[4];
#pragma unroll
          for (int i = 0; i < 4; i++) {
            const int e = 4 * j + i;
            q[i] = hadd2(pack2(acc[2 * e], acc[2 * e + 1]), yr[e]);
          }
          stsm4t(sb + OFF_W + 5 * 8192 + to + j * 2048, q[0], q[1], q[2], q[3]);
        }
        fence_async_smem();
        asm volatile("bar.arrive %0, 160;" ::"r"(1 + hf) : "memory");
      }
    }
  }
  __syncwarp();
  TREND();
}

typedef CUresult (*EncodeFn)(CUtensorMap*, CUtensorMapDataType, cuuint32_t, void*, const cuuint64_t*, const cuuint64_t*, const cuuint32_t*,
                             const cuuint32_t*, CUtensorMapInterleave, CUtensorMapSwizzle, CUtensorMapL2promotion, CUtensorMapFloatOOBfill);

void make_map(EncodeFn enc, CUtensorMap* m, const void* p, int cols, int rows, int bc, int br, bool swz) {
  cuuint64_t gd[2] = {(cuuint64_t)cols, (cuuint64_t)rows}, gs[1] = {(cuuint64_t)cols * 2};
  cuuint32_t box[2] = {(cuuint32_t)bc, (cuuint32_t)br}, es[2] = {1, 1};
  enc(m, CU_TENSOR_MAP_DATA_TYPE_BFLOAT16, 2, const_cast<void*>(p), gd, gs, box, es, CU_TENSOR_MAP_INTERLEAVE_NONE,
      swz ? CU_TENSOR_MAP_SWIZZLE_128B : CU_TENSOR_MAP_SWIZZLE_NONE, CU_TENSOR_MAP_L2_PROMOTION_L2_128B, CU_TENSOR_MAP_FLOAT_OOB_FILL_NONE);
}

}

extern "C" void kernel_launch(void* const* d_in, const int* in_sizes, int n_in, void* d_out, int out_size) {
  EncodeFn enc = nullptr;
  cudaDriverEntryPointQueryResult qr;
  cudaGetDriverEntryPoint("cuTensorMapEncodeTiled", (void**)&enc, cudaEnableDefault, &qr);
  void* scr;
  cudaGetSymbolAddress(&scr, g_scr);
  uint8_t *xt = (uint8_t*)scr + G_XT, *yt = (uint8_t*)scr + G_YT, *wext = (uint8_t*)scr + G_WEXT;
  Params p;
  make_map(enc, &p.x, d_in[0], D_, T_, 64, 128, true);
  make_map(enc, &p.wg, d_in[10], F_, D_, 64, 32, true);
  make_map(enc, &p.wu, d_in[11], F_, D_, 64, 32, true);
  make_map(enc, &p.wext, wext, 1536, 32, 64, 16, true);
  make_map(enc, &p.w2, d_in[12], D_, F_, 64, 64, true);
  make_map(enc, &p.w2s, d_in[12], D_, F_, 64, 48, true);
  make_map(enc, &p.xt, xt, 8192, 128, 64, 128 / XP, true);
  make_map(enc, &p.yt, yt, T_, D_, 64, 64, true);
  make_map(enc, &p.out, d_out, D_, T_, 64, 32, true);
  {
    cuuint64_t gd[3] = {64, T_, 8}, gs[2] = {D_ * 2, 128};
    cuuint32_t box[3] = {64, 16, 8}, es[3] = {1, 1, 1};
    enc(&p.xln, CU_TENSOR_MAP_DATA_TYPE_BFLOAT16, 3, d_in[0], gd, gs, box, es, CU_TENSOR_MAP_INTERLEAVE_NONE, CU_TENSOR_MAP_SWIZZLE_128B,
        CU_TENSOR_MAP_L2_PROMOTION_L2_128B, CU_TENSOR_MAP_FLOAT_OOB_FILL_NONE);
  }
  p.scr = (uint8_t*)scr;
  for (int i = 0; i < 7; i++) p.ssm[i] = (const __nv_bfloat16*)d_in[1 + i];
  p.dskip = (const __nv_bfloat16*)d_in[8];
  cudaFuncSetAttribute(fused_kernel, cudaFuncAttributeMaxDynamicSharedMemorySize, SMEM_BYTES);
  fused_kernel<<<128, NTHREADS, SMEM_BYTES>>>(p);
}
```
